```python
import torch

def _softmax(x, axis=-1):
    return torch.softmax(x, dim=axis)
def _gelu(x):
    return torch.nn.functional.gelu(x, approximate="tanh")
def _silu(x):
    return torch.nn.functional.silu(x)
def _sigmoid(x):
    return torch.sigmoid(x)
def _layernorm(x, axis=-1, eps=1e-5):
    m = x.mean(dim=axis, keepdim=True)
    v = x.var(dim=axis, keepdim=True, unbiased=False)
    return (x - m) / torch.sqrt(v + eps)
def _scatter_add(tgt, idx, src, axis=0):
    return tgt.clone().index_add_(axis, idx, src)
def _segment_sum(src, seg, n):
    out = torch.zeros((n,) + src.shape[1:], dtype=src.dtype)
    return out.index_add_(0, seg, src)
def _pad(x, pw):
    flat = tuple(v for pair in reversed(pw) for v in pair)
    return torch.nn.functional.pad(x, flat)

kernel_name = 'standalone__cheap_equivariant_egnn__graph'

def setup_inputs():

    _w = (lambda a: (lambda t: t.to(torch.bfloat16) if t.is_floating_point() else t)(torch.as_tensor(a)))
    N, deg, D, De = 50000, 16, 64, max(0, 1)
    E = N * deg
    return {
        "h": _w((lambda *s: torch.randn(*s, dtype=torch.bfloat16) * 0.2)(N, D)),
        "pos": _w((lambda *s: torch.randn(*s, dtype=torch.bfloat16) * 0.4)(N, 3)),
        "e_attr": _w((lambda *s: torch.randn(*s, dtype=torch.bfloat16) * 0.4)(E, De)),
        "src": _w((lambda lo, hi, *s: torch.randint(lo, hi, s))(0, N, E).to(torch.int64)),
        "dst": _w((lambda lo, hi, *s: torch.randint(lo, hi, s))(0, N, E).to(torch.int64)),
        "w_e": _w(0.1 * (lambda *s: torch.randn(*s, dtype=torch.bfloat16) * 0.4)(2 * D + 1 + De, D)),
        "w_x": _w(0.1 * (lambda *s: torch.randn(*s, dtype=torch.bfloat16) * 0.2)(D, 1)),
        "w_h": _w(0.1 * (lambda *s: torch.randn(*s, dtype=torch.bfloat16) * 0.2)(2 * D, D)),
    }

def reference(h, pos, e_attr, src, dst, w_e, w_x, w_h):
    N, D = h.shape[0], h.shape[1]
    diff = pos[dst] - pos[src]
    dist2 = torch.sum(diff * diff, axis=-1, keepdims=True)
    e_in = torch.concatenate([h[dst], h[src], dist2, e_attr], axis=-1)
    m_ij = _silu(e_in @ w_e)
    coord_scale = m_ij @ w_x
    pos_new = pos + _segment_sum(diff * coord_scale, dst, N)
    m_i = _segment_sum(m_ij, dst, N)
    h_new = h + _silu(torch.concatenate([h, m_i], axis=-1) @ w_h)
    return h_new, pos_new
```

```cpp
#include <cuda.h>
#include <cuda_runtime.h>
#include <cuda_bf16.h>
#include <cuda_fp16.h>
#include <stdint.h>

namespace {

constexpr int N_NODES = 50000;
constexpr int N_EDGES = 800000;
constexpr int NT = 512;
constexpr int NW = NT / 32;
constexpr int NPP = 384;
constexpr int NP = (N_NODES + NPP - 1) / NPP;
constexpr int EPT = 12;
constexpr int CH = NT * EPT;
constexpr int CELL = 80;
constexpr int CELLU = CELL / 2;
constexpr int CAPN = 46;
constexpr int MAXD = CAPN - 4;
constexpr int MAILW = 32;
constexpr uint32_t KILL = NP * NPP;
constexpr int BROWS = NP * NPP + 8;
constexpr int NCW = 8;
constexpr int RPW = (NP + NCW - 1) / NCW;
static_assert(NP * CH >= N_EDGES, "chunks must cover the edge list");
static_assert(N_EDGES % 4 == 0 && KILL < 65536, "shape assumptions");
static_assert(NP <= 144 && RPW <= 18, "loop bounds");

constexpr uint32_t SB = 2048;
constexpr uint32_t SM_H = SB;
constexpr uint32_t SM_W = SM_H + NPP * 128;
constexpr uint32_t SM_A = SM_W + 4 * 8192;
constexpr uint32_t SM_REC = SM_A + NPP * 128;
constexpr uint32_t SM_STAGE = SM_A;
constexpr uint32_t SM_POS = SM_REC + NPP * CAPN * 4;
constexpr uint32_t SM_CNT1 = SM_POS + NPP * 8;
constexpr uint32_t SM_CNT2 = SM_CNT1 + 160 * 4;
constexpr uint32_t SM_HIST = SM_CNT2 + NPP * 4;
constexpr uint32_t SM_FLAG = SM_HIST + 32 * 4;
constexpr uint32_t SM_DUMMY = SM_FLAG + 64;
constexpr uint32_t SM_RUN = SM_DUMMY + 128;
constexpr uint32_t SM_ORD = SM_RUN + 160 * 4;
constexpr uint32_t SM_SLOW = SM_ORD + NPP * 4;
constexpr uint32_t SM_BAR = SM_SLOW + NPP * 4;
constexpr uint32_t SM_CONST = SM_BAR + 32;
constexpr uint32_t SM_END = SM_CONST + 5 * 512;
static_assert(RPW * NCW * CELL * 8 <= NPP * 128 + NPP * CAPN * 4, "staging must fit");
static_assert(SM_A % 1024 == 0 && SM_W % 1024 == 0 && SM_REC % 16 == 0 && SM_CONST % 16 == 0 && SM_CNT1 % 16 == 0, "alignment");
constexpr uint32_t F_BIG = SM_FLAG, F_GBIG = SM_FLAG + 4, F_SLOW = SM_FLAG + 8, F_NSLOW = SM_FLAG + 12,
                   F_WDM = SM_FLAG + 16, F_NOVF = SM_FLAG + 20;

__device__ uint4 g_cell[(NP * NP + 128) * CELLU];
__device__ uint2 g_ovf[NP * CH];
__device__ __align__(1024) uint4 g_B[2 * BROWS * 4];
__device__ uint32_t g_mail[NP * MAILW];
__device__ uint32_t g_epoch[NP];
#define TSTAMP_T(i, th)
#define TSTAMP(i) TSTAMP_T(i, 0)

__device__ __forceinline__ void hmma16_h(uint32_t& d0, uint32_t& d1, uint32_t a0, uint32_t a1, uint32_t a2, uint32_t a3,
                                         uint32_t b0, uint32_t b1, uint32_t c0, uint32_t c1) {
    asm("mma.sync.aligned.m16n8k16.row.col.f16.f16.f16.f16 {%0,%1}, {%2,%3,%4,%5}, {%6,%7}, {%8,%9};"
        : "=r"(d0), "=r"(d1) : "r"(a0), "r"(a1), "r"(a2), "r"(a3), "r"(b0), "r"(b1), "r"(c0), "r"(c1));
}
__device__ __forceinline__ void hmma8_h(uint32_t& d0, uint32_t& d1, uint32_t a0, uint32_t a1, uint32_t b0) {
    asm("mma.sync.aligned.m16n8k8.row.col.f16.f16.f16.f16 {%0,%1}, {%2,%3}, {%4}, {%0,%1};"
        : "+r"(d0), "+r"(d1) : "r"(a0), "r"(a1), "r"(b0));
}
__device__ __forceinline__ void hmma16_f(float (&d)[4], uint32_t a0, uint32_t a1, uint32_t a2, uint32_t a3,
                                         uint32_t b0, uint32_t b1) {
    asm("mma.sync.aligned.m16n8k16.row.col.f32.f16.f16.f32 {%0,%1,%2,%3}, {%4,%5,%6,%7}, {%8,%9}, {%0,%1,%2,%3};"
        : "+f"(d[0]), "+f"(d[1]), "+f"(d[2]), "+f"(d[3])
        : "r"(a0), "r"(a1), "r"(a2), "r"(a3), "r"(b0), "r"(b1));
}
__host__ __device__ constexpr uint64_t mkdesc(uint32_t addr) {
    return (uint64_t)((addr & 0x3FFFF) >> 4) | ((uint64_t)1 << 16) | ((uint64_t)64 << 32) | ((uint64_t)1 << 62);
}
__device__ __forceinline__ void wg_fence() { asm volatile("wgmma.fence.sync.aligned;" ::: "memory"); }
__device__ __forceinline__ void wg_commit() { asm volatile("wgmma.commit_group.sync.aligned;" ::: "memory"); }
__device__ __forceinline__ void wg_wait0() { asm volatile("wgmma.wait_group.sync.aligned 0;" ::: "memory"); }
template <int ACC>
__device__ __forceinline__ void wg_n64(float (&d)[32], uint64_t da, uint64_t db) {
    asm volatile("{.reg .pred p; setp.ne.b32 p, %34, 0;\n"
        "wgmma.mma_async.sync.aligned.m64n64k16.f32.bf16.bf16 "
        "{%0,%1,%2,%3,%4,%5,%6,%7,%8,%9,%10,%11,%12,%13,%14,%15,%16,%17,%18,%19,%20,%21,%22,%23,%24,%25,%26,%27,%28,%29,%30,%31},"
        " %32, %33, p, 1, 1, 0, 1;}"
        : "+f"(d[0]), "+f"(d[1]), "+f"(d[2]), "+f"(d[3]), "+f"(d[4]), "+f"(d[5]), "+f"(d[6]), "+f"(d[7]),
          "+f"(d[8]), "+f"(d[9]), "+f"(d[10]), "+f"(d[11]), "+f"(d[12]), "+f"(d[13]), "+f"(d[14]), "+f"(d[15]),
          "+f"(d[16]), "+f"(d[17]), "+f"(d[18]), "+f"(d[19]), "+f"(d[20]), "+f"(d[21]), "+f"(d[22]), "+f"(d[23]),
          "+f"(d[24]), "+f"(d[25]), "+f"(d[26]), "+f"(d[27]), "+f"(d[28]), "+f"(d[29]), "+f"(d[30]), "+f"(d[31])
        : "l"(da), "l"(db), "n"(ACC));
}
__device__ __forceinline__ void fence_regs(float (&d)[32]) {
#pragma unroll
    for (int i = 0; i < 32; i++) asm volatile("" : "+f"(d[i]) :: "memory");
}
__device__ __forceinline__ void fence_async() { asm volatile("fence.proxy.async.shared::cta;" ::: "memory"); }
__device__ __forceinline__ void stsm4(uint32_t addr, uint32_t r0, uint32_t r1, uint32_t r2, uint32_t r3) {
    asm volatile("stmatrix.sync.aligned.m8n8.x4.shared.b16 [%0], {%1,%2,%3,%4};"
                 :: "r"(addr), "r"(r0), "r"(r1), "r"(r2), "r"(r3) : "memory");
}
__device__ __forceinline__ void ldsm4(uint32_t (&r)[4], uint32_t addr) {
    asm volatile("ldmatrix.sync.aligned.m8n8.x4.shared.b16 {%0,%1,%2,%3}, [%4];"
                 : "=r"(r[0]), "=r"(r[1]), "=r"(r[2]), "=r"(r[3]) : "r"(addr) : "memory");
}
__device__ __forceinline__ uint32_t pack_bf(float lo, float hi) {
    uint32_t d;
    asm("cvt.rn.bf16x2.f32 %0, %1, %2;" : "=r"(d) : "f"(hi), "f"(lo));
    return d;
}
__device__ __forceinline__ uint32_t pack_h(float lo, float hi) {
    uint32_t d;
    asm("cvt.rn.f16x2.f32 %0, %1, %2;" : "=r"(d) : "f"(hi), "f"(lo));
    return d;
}
__device__ __forceinline__ uint32_t bmul2(uint32_t a, uint32_t b) {
    uint32_t d;
    asm("mul.rn.bf16x2 %0, %1, %2;" : "=r"(d) : "r"(a), "r"(b));
    return d;
}
__device__ __forceinline__ uint32_t badd2(uint32_t a, uint32_t b) {
    uint32_t d;
    asm("add.rn.bf16x2 %0, %1, %2;" : "=r"(d) : "r"(a), "r"(b));
    return d;
}
__device__ __forceinline__ uint32_t bsub2(uint32_t a, uint32_t b) {
    uint32_t d;
    asm("sub.rn.bf16x2 %0, %1, %2;" : "=r"(d) : "r"(a), "r"(b));
    return d;
}
__device__ __forceinline__ uint32_t hadd2(uint32_t a, uint32_t b) {
    uint32_t d;
    asm("add.rn.f16x2 %0, %1, %2;" : "=r"(d) : "r"(a), "r"(b));
    return d;
}
__device__ __forceinline__ uint32_t habsmax2(uint32_t a, uint32_t b) {
    uint32_t d;
    asm("max.NaN.xorsign.abs.f16x2 %0, %1, %2;" : "=r"(d) : "r"(a), "r"(b));
    return d;
}
__device__ __forceinline__ float silu_half(float x) {
    float t;
    asm("tanh.approx.f32 %0, %1;" : "=f"(t) : "f"(x));
    return fmaf(x, t, x);
}
__device__ __forceinline__ uint32_t silu_half2(uint32_t x) {
    uint32_t t, m;
    asm("tanh.approx.f16x2 %0, %1;" : "=r"(t) : "r"(x));
    asm("fma.rn.f16x2 %0, %1, %2, %1;" : "=r"(m) : "r"(x), "r"(t));
    return m;
}
__device__ __forceinline__ uint4 ldg_relaxed(const void* p) {
    uint4 v;
    asm volatile("ld.relaxed.gpu.global.v4.u32 {%0,%1,%2,%3}, [%4];"
                 : "=r"(v.x), "=r"(v.y), "=r"(v.z), "=r"(v.w) : "l"(p) : "memory");
    return v;
}
__device__ __forceinline__ uint4 ldg_cg(const void* p) {
    uint4 v;
    asm volatile("ld.global.L1::no_allocate.v4.u32 {%0,%1,%2,%3}, [%4];"
                 : "=r"(v.x), "=r"(v.y), "=r"(v.z), "=r"(v.w) : "l"(p) : "memory");
    return v;
}
__device__ __forceinline__ uint4 ldg_nc(const void* p) {
    uint4 v;
    asm volatile("ld.global.nc.L1::no_allocate.v4.u32 {%0,%1,%2,%3}, [%4];"
                 : "=r"(v.x), "=r"(v.y), "=r"(v.z), "=r"(v.w) : "l"(p));
    return v;
}
__device__ __forceinline__ uint2 ldg_nc2(const void* p) {
    uint2 v;
    asm volatile("ld.global.nc.L1::no_allocate.v2.u32 {%0,%1}, [%2];" : "=r"(v.x), "=r"(v.y) : "l"(p));
    return v;
}
__device__ __forceinline__ uint32_t bf16_bits(const __nv_bfloat16* p) {
    return (uint32_t)__ldg(reinterpret_cast<const unsigned short*>(p));
}
__device__ __forceinline__ float bf16_val(const __nv_bfloat16* p) { return __uint_as_float(bf16_bits(p) << 16); }
__device__ __forceinline__ uint4 tex_row(cudaTextureObject_t tex, uint32_t i) {
    uint4 v;
    asm volatile("tex.1d.v4.u32.s32 {%0,%1,%2,%3}, [%4, {%5}];"
                 : "=r"(v.x), "=r"(v.y), "=r"(v.z), "=r"(v.w) : "l"(tex), "r"(i));
    return v;
}
__device__ __forceinline__ uint32_t lds16(uint32_t addr) {
    uint32_t v;
    asm volatile("ld.shared.u16 %0, [%1];" : "=r"(v) : "r"(addr) : "memory");
    return v;
}
__device__ __forceinline__ uint32_t lds32(uint32_t addr) {
    uint32_t v;
    asm volatile("ld.shared.u32 %0, [%1];" : "=r"(v) : "r"(addr) : "memory");
    return v;
}
__device__ __forceinline__ uint2 lds64(uint32_t addr) {
    uint2 v;
    asm volatile("ld.shared.v2.u32 {%0,%1}, [%2];" : "=r"(v.x), "=r"(v.y) : "r"(addr) : "memory");
    return v;
}
__device__ __forceinline__ uint4 lds128(uint32_t addr) {
    uint4 v;
    asm volatile("ld.shared.v4.u32 {%0,%1,%2,%3}, [%4];" : "=r"(v.x), "=r"(v.y), "=r"(v.z), "=r"(v.w) : "r"(addr) : "memory");
    return v;
}
__device__ __forceinline__ void sts32(uint32_t addr, uint32_t v) {
    asm volatile("st.shared.u32 [%0], %1;" :: "r"(addr), "r"(v) : "memory");
}
__device__ __forceinline__ void sts64(uint32_t addr, uint32_t a, uint32_t b) {
    asm volatile("st.shared.v2.u32 [%0], {%1,%2};" :: "r"(addr), "r"(a), "r"(b) : "memory");
}
__device__ __forceinline__ void sts128(uint32_t addr, uint32_t a, uint32_t b, uint32_t c, uint32_t d) {
    asm volatile("st.shared.v4.u32 [%0], {%1,%2,%3,%4};" :: "r"(addr), "r"(a), "r"(b), "r"(c), "r"(d) : "memory");
}
__device__ __forceinline__ uint32_t atom_inc(uint32_t addr) {
    uint32_t r;
    asm volatile("atom.shared.add.u32 %0, [%1], 1;" : "=r"(r) : "r"(addr) : "memory");
    return r;
}
__device__ __forceinline__ void sts32_lt(uint32_t a, uint32_t b, uint32_t addr, uint32_t v) {
    asm volatile("{.reg .pred q; setp.lt.u32 q, %2, %3; @q st.shared.u32 [%0], %1;}"
                 :: "r"(addr), "r"(v), "r"(a), "r"(b) : "memory");
}
__device__ __forceinline__ void sts64_lt(uint32_t a, uint32_t b, uint32_t addr, uint32_t x, uint32_t y) {
    asm volatile("{.reg .pred q; setp.lt.u32 q, %3, %4; @q st.shared.v2.u32 [%0], {%1,%2};}"
                 :: "r"(addr), "r"(x), "r"(y), "r"(a), "r"(b) : "memory");
}
__device__ __forceinline__ uint32_t and3(uint32_t a, uint32_t b, uint32_t c) {
    uint32_t d;
    asm("lop3.b32 %0, %1, %2, %3, 0x80;" : "=r"(d) : "r"(a), "r"(b), "r"(c));
    return d;
}
template <uint32_t M>
__device__ __forceinline__ uint32_t bitsel(uint32_t a, uint32_t b) {
    uint32_t d;
    asm("lop3.b32 %0, %1, %2, %3, 0xE4;" : "=r"(d) : "r"(a), "r"(b), "n"(M));
    return d;
}
__device__ __forceinline__ uint32_t extract16(const uint4& r, uint32_t four) {
    const uint32_t u = bitsel<0x00030003u>(r.x, r.y * four);
    const uint32_t v = bitsel<0x00030003u>(r.z, r.w * four);
    const uint32_t w = bitsel<0x000F000Fu>(u, v << 4);
    return __byte_perm(w, 0u, 0x2044);
}
__device__ __forceinline__ float bfr(float x) { return __bfloat162float(__float2bfloat16(x)); }
__device__ __forceinline__ void mbar_wait(uint32_t bar) {
    uint32_t done = 0;
    int spin = 0;
    while (!done) {
        asm volatile("{.reg .pred p; mbarrier.try_wait.parity.shared.b64 p, [%1], 0; selp.u32 %0, 1, 0, p;}"
                     : "=r"(done) : "r"(bar) : "memory");
        if (++spin > (1 << 24)) __trap();
    }
}
__device__ __forceinline__ void tma_load(uint32_t dst, const CUtensorMap* tm, int row, uint32_t bar) {
    asm volatile("cp.async.bulk.tensor.2d.shared::cluster.global.mbarrier::complete_tx::bytes [%0], [%1, {%3, %4}], [%2];"
                 :: "r"(dst), "l"(tm), "r"(bar), "r"(0), "r"(row) : "memory");
}
__device__ __forceinline__ void tma_store(const CUtensorMap* tm, int row, uint32_t src) {
    asm volatile("cp.async.bulk.tensor.2d.global.shared::cta.bulk_group [%0, {%2, %3}], [%1];"
                 :: "l"(tm), "r"(src), "r"(0), "r"(row) : "memory");
}
__device__ __forceinline__ uint32_t poll_mail(int run, uint32_t tag) {
    uint32_t v;
    int spin = 0;
    while (true) {
        asm volatile("ld.acquire.gpu.global.u32 %0, [%1];" : "=r"(v) : "l"(&g_mail[run * MAILW]) : "memory");
        if ((v ^ tag) < 0x10000u) break;
        if (++spin > (1 << 24)) __trap();
    }
    return v;
}
__device__ __forceinline__ void place_rec(uint32_t x, uint32_t ln) {
    const uint32_t rk = atom_inc(SM_CNT2 + ln * 4);
    sts32_lt(rk, CAPN, SM_REC + (ln * CAPN + rk) * 4, x);
}
__device__ __forceinline__ int uniform_warp() { return __shfl_sync(0xffffffffu, threadIdx.x >> 5, 0); }

__device__ __noinline__ void slow_node(int ln, const __nv_bfloat16* h, const __nv_bfloat16* pos,
                                       const __nv_bfloat16* w_e, const __nv_bfloat16* w_x, __nv_bfloat16* out) {
    const int lane = threadIdx.x & 31, c = 2 * lane;
    const int node = blockIdx.x * NPP + ln;
    float a0 = 0.f, a1 = 0.f;
#pragma unroll 4
    for (int k = 0; k < 64; k++) {
        const float hv = bf16_val(h + (size_t)node * 64 + k);
        a0 = fmaf(hv, bf16_val(w_e + k * 64 + c), a0);
        a1 = fmaf(hv, bf16_val(w_e + k * 64 + c + 1), a1);
    }
    const float wd0 = bf16_val(w_e + 128 * 64 + c), wd1 = bf16_val(w_e + 128 * 64 + c + 1);
    const float wa0 = bf16_val(w_e + 129 * 64 + c), wa1 = bf16_val(w_e + 129 * 64 + c + 1);
    const float wx0 = bf16_val(w_x + c), wx1 = bf16_val(w_x + c + 1);
    const float px = bf16_val(pos + (size_t)node * 3), py = bf16_val(pos + (size_t)node * 3 + 1),
                pz = bf16_val(pos + (size_t)node * 3 + 2);
    float m0 = 0.f, m1 = 0.f, ux = 0.f, uy = 0.f, uz = 0.f;
    for (int run = 0; run < NP; run++) {
        const int novf = lds32(SM_RUN + run * 4) & 0x1fff;
        const uint2* cell = reinterpret_cast<const uint2*>(g_cell + ((size_t)blockIdx.x * NP + run) * CELLU);
        const int ncell = min((int)(__ldcg(cell).y & 0xffffu) + 1, CELL);
        for (int i0 = 0; i0 < 96 + novf; i0 += 32) {
            const int i = i0 + lane;
            uint2 rec = make_uint2(0u, 0u);
            bool hit = false;
            if (i >= 1 && i < ncell) {
                rec = __ldcg(cell + i);
                hit = (rec.y & 511u) == (uint32_t)ln;
            } else if (i >= 96 && i - 96 < novf) {
                rec = __ldcg(g_ovf + (size_t)run * CH + i - 96);
                hit = rec.y == (uint32_t)node;
            }
            uint32_t bal = __ballot_sync(0xffffffffu, hit);
            while (bal) {
                const int l = __ffs(bal) - 1;
                bal &= bal - 1;
                const uint32_t rx = __shfl_sync(0xffffffffu, rec.x, l);
                const int s = rx & 0xffff;
                const float ea = __uint_as_float(rx & 0xffff0000u);
                float b0 = a0, b1 = a1;
#pragma unroll 8
                for (int k = 0; k < 64; k++) {
                    const float hv = bf16_val(h + (size_t)s * 64 + k);
                    b0 = fmaf(hv, bf16_val(w_e + (64 + k) * 64 + c), b0);
                    b1 = fmaf(hv, bf16_val(w_e + (64 + k) * 64 + c + 1), b1);
                }
                const float dx = bfr(px - bf16_val(pos + (size_t)s * 3)), dy = bfr(py - bf16_val(pos + (size_t)s * 3 + 1)),
                            dz = bfr(pz - bf16_val(pos + (size_t)s * 3 + 2));
                const float d2 = dx * dx + dy * dy + dz * dz;
                b0 = fmaf(ea, wa0, fmaf(d2, wd0, b0));
                b1 = fmaf(ea, wa1, fmaf(d2, wd1, b1));
                const float s0 = b0 / (1.f + __expf(-b0)), s1 = b1 / (1.f + __expf(-b1));
                m0 += s0; m1 += s1;
                float cs = s0 * wx0 + s1 * wx1;
#pragma unroll
                for (int o = 16; o > 0; o >>= 1) cs += __shfl_xor_sync(0xffffffffu, cs, o);
                ux = fmaf(dx, cs, ux); uy = fmaf(dy, cs, uy); uz = fmaf(dz, cs, uz);
            }
        }
    }
    sts32(SM_A + ln * 128 + (((lane >> 2) ^ (ln & 7)) << 4) + (lane & 3) * 4, pack_bf(m0, m1));
    if (lane == 0) {
        __nv_bfloat16* pp = out + (size_t)N_NODES * 64 + (size_t)node * 3;
        pp[0] = __float2bfloat16(px + ux); pp[1] = __float2bfloat16(py + uy); pp[2] = __float2bfloat16(pz + uz);
    }
}
__device__ __noinline__ void collect_tail(int run, uint32_t tag, bool with_tail) {
    const int lane = threadIdx.x & 31, u = 32 + lane;
    const uint4* cell = g_cell + ((size_t)blockIdx.x * NP + run) * CELLU;
    uint4 v = ldg_relaxed(cell + (lane < 8 ? u : 0));
    const uint32_t cnt = (__shfl_sync(0xffffffffu, v.y, 8) & 0xffffu) + 1, n = min(cnt, (uint32_t)CELL);
    if (with_tail && 2u * u < n) {
        int spin = 0;
        while ((v.y ^ tag) >= 0x10000u) {
            v = ldg_relaxed(cell + u);
            if (++spin > (1 << 24)) __trap();
        }
        place_rec(v.x, v.y & 511u);
        if (2u * u + 1 < n) place_rec(v.z, v.w & 511u);
    }
    __syncwarp();
    if (cnt > (uint32_t)CELL) {
        const int novf = poll_mail(run, tag) & 0x1fff;
        for (int i = lane; i < novf; i += 32) {
            const uint2 r = __ldcg(g_ovf + (size_t)run * CH + i);
            const uint32_t ln = r.y - blockIdx.x * NPP;
            if (ln < (uint32_t)NPP) place_rec(r.x, ln);
        }
    }
    __syncwarp();
}

__device__ __forceinline__ void const_phase(const __nv_bfloat16* w_e, const __nv_bfloat16* w_x) {
    const int lane = threadIdx.x & 31, g = lane >> 2, t = lane & 3;
    const float wd0 = fabsf(bf16_val(w_e + 128 * 64 + lane)), wd1 = fabsf(bf16_val(w_e + 128 * 64 + 32 + lane));
    const float wa0 = fabsf(bf16_val(w_e + 129 * 64 + lane)), wa1 = fabsf(bf16_val(w_e + 129 * 64 + 32 + lane));
    float wgf[8], wxf[16];
    const __nv_bfloat16* wr = w_e + (t < 3 ? 128 : 129) * 64 + g;
#pragma unroll
    for (int i = 0; i < 8; i++) wgf[i] = 0.5f * bf16_val(wr + 8 * i);
    float wxm = 0.f;
#pragma unroll
    for (int i = 0; i < 16; i++) {
        wxf[i] = bf16_val(w_x + 8 * (i >> 1) + 2 * t + (i & 1));
        wxm = fmaxf(wxm, fabsf(wxf[i]));
    }
    const float wdm = __uint_as_float(__reduce_max_sync(0xffffffffu, __float_as_uint(fmaxf(wd0, wd1))));
    const float wam = __uint_as_float(__reduce_max_sync(0xffffffffu, __float_as_uint(fmaxf(wa0, wa1))));
    const uint32_t wxe = min(max(__reduce_max_sync(0xffffffffu, __float_as_uint(wxm)) >> 23, 2u), 252u);
    const float sc = __uint_as_float((254u - wxe) << 23);
    if (!(wdm == 0.f || (wdm >= 1.953125e-3f && wdm <= 32.f)) || !(wam == 0.f || (wam >= 1.953125e-3f && wam <= 32.f)))
        sts32(F_SLOW, 1u);
    sts32(F_WDM, __float_as_uint(wdm));
    const uint32_t ad = SM_CONST + lane * 16;
    sts128(ad, pack_h(wgf[0], wgf[1]), pack_h(wgf[2], wgf[3]), pack_h(wgf[4], wgf[5]), pack_h(wgf[6], wgf[7]));
#pragma unroll
    for (int i = 0; i < 2; i++)
        sts128(ad + 512 + 512 * i, pack_h(sc * wxf[8 * i], sc * wxf[8 * i + 1]), pack_h(sc * wxf[8 * i + 2], sc * wxf[8 * i + 3]),
               pack_h(sc * wxf[8 * i + 4], sc * wxf[8 * i + 5]), pack_h(sc * wxf[8 * i + 6], sc * wxf[8 * i + 7]));
    sts128(ad + 1536, 0u, 0u, 0u, 0u);
    sts128(ad + 2048, ((g >> 1) == t) ? (0x3C00u << (16 * (g & 1))) : 0u, ((g >> 1) == t) ? 0x3f800000u : 0u,
           t == 3 ? 0xffff0000u : 0u, wxe << 23);
}

__device__ __forceinline__ void node_phase(uint32_t tag, const __nv_bfloat16* w_e, const __nv_bfloat16* w_x) {
    const int lane = threadIdx.x & 31, g = lane >> 2, t = lane & 3;
    const int warp = uniform_warp(), wg = warp >> 2;
    const int row = wg * 192 + (warp & 3) * 16 + g;
    float acc[3][32];
    auto gemm = [&](uint32_t w) {
        const uint64_t da = mkdesc(SM_H) + wg * (3 * 512);
        wg_fence();
#pragma unroll
        for (int j = 0; j < 3; j++) {
            wg_n64<0>(acc[j], da + j * 512, mkdesc(w));
#pragma unroll
            for (int kk = 1; kk < 4; kk++) wg_n64<1>(acc[j], da + j * 512 + kk * 2, mkdesc(w + kk * 2048));
        }
        wg_commit();
        wg_wait0();
#pragma unroll
        for (int j = 0; j < 3; j++) fence_regs(acc[j]);
    };
    uint32_t c[6];
#pragma unroll
    for (int i = 0; i < 6; i++)
        c[i] = __byte_perm(lds16(SM_POS + row * 8 + 2 * t + (i >> 1) * 512 + (i & 1) * 64), 0u, 0x4140);
    mbar_wait(SM_BAR);
    TSTAMP(17);
    gemm(SM_W + 8192);
    if (fmaxf(fabsf(acc[0][0]), fabsf(acc[1][31])) >= 9.765625e-4f) sts32(F_BIG, 0x8000u);
    asm volatile("bar.sync 8, %0;" :: "n"(NT) : "memory");
#pragma unroll
    for (int i = 0; i < 6; i++) {
        const float* a = acc[i >> 1] + 2 * (i & 1);
        const uint32_t ad = SM_A + row * 64 + t * 16 + (i >> 1) * 4096 + (i & 1) * 512;
        sts128(ad, bitsel<0x00030003u>(c[i], pack_h(a[0], a[1])), bitsel<0x00030003u>(c[i] >> 2, pack_h(a[4], a[5])),
               bitsel<0x00030003u>(c[i] >> 4, pack_h(a[8], a[9])), bitsel<0x00030003u>(c[i] >> 6, pack_h(a[12], a[13])));
        sts128(ad + NPP * 64, pack_h(a[16], a[17]), pack_h(a[20], a[21]), pack_h(a[24], a[25]), pack_h(a[28], a[29]));
    }
    fence_async();
    auto store_B = [&](int c) {
        asm volatile("cp.async.bulk.global.shared::cta.bulk_group [%0], [%1], %2;"
                     :: "l"(g_B + ((size_t)(c / 3) * BROWS + blockIdx.x * NPP + (c % 3) * 128) * 4), "r"(SM_A + c * 8192),
                        "r"(8192) : "memory");
        asm volatile("cp.async.bulk.commit_group;" ::: "memory");
    };
    if (warp != 0) {
        asm volatile("bar.arrive 1, 256;" ::: "memory");
    } else {
        asm volatile("bar.sync 1, 256;" ::: "memory");
        if (lane == 0) { store_B(0); store_B(1); }
        __syncwarp();
    }
    TSTAMP(4);
    gemm(SM_W);
    uint32_t aw[3][16], amax = 0;
#pragma unroll
    for (int j = 0; j < 3; j++) {
#pragma unroll
        for (int i = 0; i < 16; i++) {
            const int e = i >> 2, q = i & 3;
            aw[j][i] = pack_h(acc[j][8 * q + e], acc[j][8 * q + 4 + e]);
            amax = habsmax2(amax, aw[j][i]);
        }
    }
    if ((amax & 0x7fffu) > 0x7000u || (amax & 0x7fff0000u) > 0x70000000u) sts32(F_SLOW, 1u);
    if (warp == 0) {
        TSTAMP(13);
        if (lane == 0) {
#pragma unroll 1
            for (int c = 2; c < 6; c++) {
                asm volatile("cp.async.bulk.wait_group.read 1;" ::: "memory");
                store_B(c);
            }
            asm volatile("cp.async.bulk.wait_group 0;" ::: "memory");
        }
        __syncwarp();
        asm volatile("bar.arrive 2, 256;" ::: "memory");
        if (lane == 0)
            asm volatile("st.release.gpu.global.u32 [%0], %1;"
                         :: "l"(&g_mail[blockIdx.x * MAILW]), "r"(tag | lds32(F_BIG) | lds32(F_NOVF)) : "memory");
        __syncwarp();
    } else {
        if (warp == 1) const_phase(w_e, w_x);
        asm volatile("bar.sync 2, 256;" ::: "memory");
    }
#pragma unroll
    for (int j = 0; j < 3; j++) {
#pragma unroll
        for (int e = 0; e < 4; e++)
            sts128(SM_A + row * 128 + j * 8192 + (e >> 1) * 1024 + (((2 * t + (e & 1)) ^ g) << 4),
                   aw[j][4 * e], aw[j][4 * e + 1], aw[j][4 * e + 2], aw[j][4 * e + 3]);
    }
}

__device__ __noinline__ void collect_phase(uint32_t tag) {
    const int lane = threadIdx.x & 31, cw = uniform_warp() - 8;
    {
        const int myp = cw + lane * NCW;
        uint32_t n = 0;
        if (lane < RPW && myp < NP) n = lds32(SM_CNT1 + myp * 4);
        const uint32_t sp = SM_STAGE + (cw * CELLU + lane) * 16;
        uint4* gp = g_cell + ((size_t)cw * NP + blockIdx.x) * CELLU + lane;
        uint4 v[RPW];
#pragma unroll
        for (int j = 0; j < RPW; j++) v[j] = lds128(sp + j * (NCW * CELLU * 16));
        uint32_t big = __ballot_sync(0xffffffffu, n > 64);
        while (big) {
            const int j = __ffs(big) - 1;
            big &= big - 1;
            if (lane < 8) gp[(size_t)j * (NCW * NP * CELLU) + 32] = lds128(sp + j * (NCW * CELLU * 16) + 512);
        }
#pragma unroll
        for (int j = 0; j < RPW; j++) {
            const uint32_t nj = __shfl_sync(0xffffffffu, n, j);
            if (lane == 0) v[j].y = tag | (nj - 1);
            v[j].w = nj > 2u * (lane & ~1) ? v[j].w : 0u;
            if (nj > 2u * (lane & ~1)) v[j].w |= 0x10000u;
        }
        asm volatile("bar.arrive 8, %0;" :: "n"(NT) : "memory");
        asm volatile("bar.sync 3, 256;" ::: "memory");
#pragma unroll
        for (int j = 0; j < RPW; j++)
            if (v[j].w != 0) gp[(size_t)j * (NCW * NP * CELLU)] = v[j];
    }
    TSTAMP_T(3, 256);
    const uint32_t thrl = tag | (2 * lane), thr0 = lane == 0 ? 0xffffffffu : thrl, thr1 = thrl + 1;
    const uint4* cellp = g_cell + ((size_t)blockIdx.x * NP + cw) * CELLU + lane;
    uint32_t hdr = 0;
    if (lane < RPW && cw + lane * NCW < NP) {
        const uint32_t* hp = reinterpret_cast<const uint32_t*>(cellp - lane + lane * (NCW * CELLU)) + 1;
        int spin = 0;
        do {
            asm volatile("ld.relaxed.gpu.global.u32 %0, [%1];" : "=r"(hdr) : "l"(hp) : "memory");
            if (++spin > (1 << 24)) __trap();
        } while ((hdr ^ tag) >= 0x10000u);
    }
    __syncwarp();
    TSTAMP_T(12, 256);
    uint32_t big = __ballot_sync(0xffffffffu, hdr >= (tag | 64u));
    uint4 rec[RPW];
    uint32_t y0[RPW];
#pragma unroll
    for (int j = 0; j < RPW; j++) {
        y0[j] = __shfl_sync(0xffffffffu, hdr, j);
        rec[j].y = tag;
        if (y0[j] >= thrl) rec[j] = ldg_cg(cellp + j * (NCW * CELLU));
    }
    const uint32_t dummy = SM_DUMMY + lane * 4;
    if (big) {
        uint32_t m = big;
#pragma unroll
        for (int k = 1; k < 4; k++) m = (lane >> 3) >= k ? m & (m - 1) : m;
        const int j = m ? __ffs(m) - 1 : 0;
        const uint32_t hj = __shfl_sync(0xffffffffu, hdr, j), u = 32 + (lane & 7);
        const uint32_t n = m ? min((hj & 0xffffu) + 1, (uint32_t)CELL) : 0u;
        uint4 v;
        if (2 * u < n) {
            int spin = 0;
            do {
                v = ldg_relaxed(cellp - lane + j * (NCW * CELLU) + u);
                if (++spin > (1 << 24)) __trap();
            } while ((v.y ^ tag) >= 0x10000u);
        }
        if (2 * u < n) place_rec(v.x, v.y & 511u);
        if (2 * u + 1 < n) place_rec(v.z, v.w & 511u);
#pragma unroll
        for (int k = 0; k < 4; k++) big &= big - 1;
        __syncwarp();
    }
    const uint32_t huge = __ballot_sync(0xffffffffu, hdr >= (tag | (uint32_t)CELL));
#pragma unroll
    for (int b = 0; b < RPW; b += 6) {
        uint32_t rk[6][2];
        uint32_t stale = 0;
#pragma unroll
        for (int j = b; j < b + 6 && j < RPW; j++) stale |= rec[j].y ^ tag;
        if (stale >= 0x10000u) {
#pragma unroll
            for (int j = b; j < b + 6 && j < RPW; j++) {
                int spin = 0;
                while ((rec[j].y ^ tag) >= 0x10000u) {
                    rec[j] = ldg_relaxed(cellp + j * (NCW * CELLU));
                    if (++spin > (1 << 24)) __trap();
                }
            }
        }
#pragma unroll
        for (int j = b; j < b + 6 && j < RPW; j++) {
            rec[j].y &= 511u; rec[j].w &= 511u;
            rk[j - b][0] = atom_inc(y0[j] >= thr0 ? SM_CNT2 + rec[j].y * 4 : dummy);
            rk[j - b][1] = atom_inc(y0[j] >= thr1 ? SM_CNT2 + rec[j].w * 4 : dummy);
        }
#pragma unroll
        for (int j = b; j < b + 6 && j < RPW; j++) {
            sts32_lt(rk[j - b][0], CAPN, SM_REC + (rec[j].y * CAPN + rk[j - b][0]) * 4, rec[j].x);
            sts32_lt(rk[j - b][1], CAPN, SM_REC + (rec[j].w * CAPN + rk[j - b][1]) * 4, rec[j].z);
        }
    }
    TSTAMP_T(14, 256);
    uint32_t rest = big | huge;
    while (rest) {
        const int j = __ffs(rest) - 1;
        rest &= rest - 1;
        collect_tail(cw + j * NCW, tag, (big >> j) & 1u);
    }
}

__device__ __noinline__ void edge_phase(cudaTextureObject_t tex0, cudaTextureObject_t tex1, __nv_bfloat16* outp, int nown) {
    const int lane = threadIdx.x & 31, g = lane >> 2, warp = uniform_warp();
    const uint32_t cb0 = SM_CONST + lane * 16;
    const uint4 cx0 = lds128(cb0 + 512), cx1 = lds128(cb0 + 1024);
    const uint32_t wx[8] = {cx0.x, cx0.y, cx0.z, cx0.w, cx1.x, cx1.y, cx1.z, cx1.w};
    const uint32_t za1 = lds32(cb0 + 1536), za2 = lds32(cb0 + 1540), zb1 = lds32(cb0 + 1544), zb2 = lds32(cb0 + 1548);
    const uint32_t id8 = lds32(cb0 + 2048), m3 = lds32(cb0 + 2056);
    const float selc = __uint_as_float(lds32(cb0 + 2052));
    const uint32_t t = (lane & 3) | za2;

    uint4 r00, r01, r10, r11;
    uint32_t ca, cb;
    uint32_t ra = 0, rb = 0;
    uint32_t ma[8], mb[8];
    float da, db;
    uint32_t wa[8] = {}, wb[8] = {}, pda, pdb;
    uint32_t acca[8], accb[8];
    float pa = 0.f, pb = 0.f;

    auto fetch = [&](uint32_t four) {
        ca = lds32(ra); cb = lds32(rb);
        ra += 8; rb += 8;
        const uint32_t ia = (ca & 0xffffu) * four + t, ib = (cb & 0xffffu) * four + t;
        r00 = tex_row(tex0, ia); r10 = tex_row(tex0, ib);
        r01 = tex_row(tex1, ia); r11 = tex_row(tex1, ib);
    };
    auto combine = [&](uint32_t four) {
        da = __uint_as_float(bsub2(pda, extract16(r00, four)));
        db = __uint_as_float(bsub2(pdb, extract16(r10, four)));
        const uint32_t xa = pack_h(fmaf(da, da, __uint_as_float(ca & m3)), selc);
        const uint32_t xb = pack_h(fmaf(db, db, __uint_as_float(cb & m3)), selc);
        hmma16_h(ma[0], ma[1], xa, za1, za2, xa, wa[0], wa[1], r00.x, r00.y);
        hmma16_h(mb[0], mb[1], xb, zb1, zb2, xb, wb[0], wb[1], r10.x, r10.y);
        hmma16_h(ma[2], ma[3], xa, za1, za2, xa, wa[2], wa[3], r00.z, r00.w);
        hmma16_h(mb[2], mb[3], xb, zb1, zb2, xb, wb[2], wb[3], r10.z, r10.w);
        hmma16_h(ma[4], ma[5], xa, za1, za2, xa, wa[4], wa[5], r01.x, r01.y);
        hmma16_h(mb[4], mb[5], xb, zb1, zb2, xb, wb[4], wb[5], r11.x, r11.y);
        hmma16_h(ma[6], ma[7], xa, za1, za2, xa, wa[6], wa[7], r01.z, r01.w);
        hmma16_h(mb[6], mb[7], xb, zb1, zb2, xb, wb[6], wb[7], r11.z, r11.w);
    };
    auto open_group = [&](int gr) {
        const uint32_t o = SM_ORD + gr * 32 + (g >> 1) * 4;
        ra = SM_REC + (g & 1) * 4 + lds16(o) * (CAPN * 4);
        rb = SM_REC + (g & 1) * 4 + lds16(o + 16) * (CAPN * 4);
    };
    auto load_group = [&](int gr) {
        const uint32_t ta = lds16(SM_ORD + gr * 32 + t * 4), tb = lds16(SM_ORD + gr * 32 + 16 + t * 4);
        const uint4 aa = lds128(SM_A + ta * 128 + ((g ^ (ta & 7)) << 4));
        const uint4 ab = lds128(SM_A + tb * 128 + ((g ^ (tb & 7)) << 4));
        const uint4 cw = lds128(SM_CONST + lane * 16);
        const uint32_t av[4] = {aa.x, aa.y, aa.z, aa.w}, bv[4] = {ab.x, ab.y, ab.z, ab.w};
        const uint32_t cv[4] = {cw.x, cw.y, cw.z, cw.w};
#pragma unroll
        for (int i = 0; i < 4; i++) {
            wa[2 * i] = __byte_perm(cv[i], av[i], 0x5410); wa[2 * i + 1] = __byte_perm(cv[i], av[i], 0x7632);
            wb[2 * i] = __byte_perm(cv[i], bv[i], 0x5410); wb[2 * i + 1] = __byte_perm(cv[i], bv[i], 0x7632);
        }
        const uint32_t o = SM_ORD + gr * 32 + (g >> 1) * 4;
        pda = lds16(SM_POS + lds16(o) * 8 + 2 * t) << 16;
        pdb = lds16(SM_POS + lds16(o + 16) * 8 + 2 * t) << 16;
    };
    auto step = [&] {
        float cs[4] = {0.f, 0.f, 0.f, 0.f};
        uint32_t four;
#pragma unroll
        for (int i = 0; i < 8; i++) {
            ma[i] = silu_half2(ma[i]);
            mb[i] = silu_half2(mb[i]);
            hmma8_h(acca[i], accb[i], ma[i], mb[i], id8);
            if (i & 1) hmma16_f(cs, ma[i - 1], mb[i - 1], ma[i], mb[i], wx[i - 1], wx[i]);
            if (i == 5) {
                four = (acca[i] & za1) | 4u;
            }
        }
        pa = fmaf(cs[0], da, pa);
        pb = fmaf(cs[2], db, pb);
        combine(four);
        fetch(four);
    };

    uint32_t badq = 0;
#pragma unroll 1
    for (int q = 0; q < 3; q++) {
        const int grp = q == 0 ? warp : 15 + 16 * q - warp;
        open_group(grp);
        const uint32_t rend = ra + 16 + lds16(SM_ORD + grp * 32 + 2) * 8;
        fetch(4u);
        load_group(grp);
        combine(4u);
        fetch((ma[0] & za1) | 4u);
#pragma unroll
        for (int i = 0; i < 8; i++) acca[i] = accb[i] = 0u;
        pa = pb = 0.f;
#pragma unroll 1
        while (ra < rend) step();
        const bool odd = g & 1;
        const uint32_t node = lds16(SM_ORD + grp * 32 + (g & 1) * 16 + (g >> 1) * 4);
        const uint32_t rn = lds16(SM_ORD + grp * 32 + (lane & 1) * 16 + ((lane >> 1) & 3) * 4);
        uint32_t mi[8], chk = 0;
#pragma unroll
        for (int i = 0; i < 8; i++) {
            const uint32_t send = odd ? acca[i] : accb[i], keep = odd ? accb[i] : acca[i];
            const uint32_t sum = hadd2(keep, __shfl_xor_sync(0xffffffffu, send, 4));
            chk = habsmax2(chk, sum);
            const __half2 s2 = *reinterpret_cast<const __half2*>(&sum);
            mi[i] = pack_bf(__low2float(s2), __high2float(s2));
        }
        const float psum = (odd ? pb : pa) + __shfl_xor_sync(0xffffffffu, odd ? pa : pb, 4);
        const bool bad = (chk & 0x7c00u) == 0x7c00u || (chk & 0x7c000000u) == 0x7c000000u ||
                         (__float_as_uint(psum) & 0x7f800000u) == 0x7f800000u;
        badq |= bad ? 1u << q : 0u;
        stsm4(SM_A + rn * 128 + (((lane >> 3) ^ (rn & 7)) << 4), mi[0], mi[1], mi[2], mi[3]);
        stsm4(SM_A + rn * 128 + (((4 + (lane >> 3)) ^ (rn & 7)) << 4), mi[4], mi[5], mi[6], mi[7]);
        const __nv_bfloat16 pn = __float2bfloat16(fmaf(psum, __uint_as_float(lds32(SM_CONST + 2060)),
                                                       __uint_as_float(lds16(SM_POS + node * 8 + 2 * t) << 16)));
        if ((int)node < nown && t < 3) outp[node * 3 + t] = pn;
    }
    if (__any_sync(0xffffffffu, badq != 0)) {
        badq |= __shfl_xor_sync(0xffffffffu, badq, 1);
        badq |= __shfl_xor_sync(0xffffffffu, badq, 2);
        if (t < 3 && ((badq >> t) & 1u)) {
            const int gr = t == 0 ? warp : t == 1 ? 31 - warp : 47 - warp;
            const uint32_t node = lds16(SM_ORD + gr * 32 + (g & 1) * 16 + (g >> 1) * 4);
            if ((int)node < nown && lds32(SM_CNT2 + node * 4) <= MAXD) sts32(SM_SLOW + atom_inc(F_NSLOW) * 4, node);
        }
    }
}

struct Maps { CUtensorMap h, out; };

__global__ void __launch_bounds__(NT, 1)
egnn_kernel(const __nv_bfloat16* __restrict__ h, const __nv_bfloat16* __restrict__ pos,
            const __nv_bfloat16* __restrict__ e_attr, const int* __restrict__ src, const int* __restrict__ dst,
            const __nv_bfloat16* __restrict__ w_e, const __nv_bfloat16* __restrict__ w_x,
            const __nv_bfloat16* __restrict__ w_h, __nv_bfloat16* __restrict__ out, cudaTextureObject_t tex0, cudaTextureObject_t tex1,
            const __grid_constant__ Maps maps) {
    extern __shared__ unsigned char smem_raw[];
    const int tid = threadIdx.x, lane = tid & 31;
    const int cta = blockIdx.x;
    const int node0 = cta * NPP;
    const int nown = min(NPP, N_NODES - node0);
    TSTAMP(0);

    uint4 vs[3], vd[3];
    uint2 ve[3];
    const int e0 = cta * CH + tid * 4;
#pragma unroll
    for (int k = 0; k < 3; k++) vd[k] = ldg_nc(dst + min(e0 + k * (NT * 4), N_EDGES - 4));
#pragma unroll
    for (int k = 0; k < 3; k++) {
        vs[k] = ldg_nc(src + min(e0 + k * (NT * 4), N_EDGES - 4));
        ve[k] = ldg_nc2(e_attr + min(e0 + k * (NT * 4), N_EDGES - 4));
    }
    const uint32_t epoch = __ldcg(&g_epoch[cta]);
    uint32_t pv[3];
    {
        const __nv_bfloat16* pp = pos + (size_t)min(node0 + tid, N_NODES - 1) * 3;
#pragma unroll
        for (int k = 0; k < 3; k++) pv[k] = bf16_bits(pp + k);
    }
    if (tid < (SM_RUN - SM_CNT1) / 16) {
        const uint32_t z = tid < (SM_CNT2 - SM_CNT1) / 16 ? 1u : tid < (SM_DUMMY - SM_CNT1) / 16 ? 0u : 1u << 16;
        sts128(SM_CNT1 + tid * 16, z, z, z, z);
    }
    uint4 wv[4];
#pragma unroll
    for (int k = 0; k < 4; k++) wv[k] = ldg_nc((k < 2 ? w_e + k * 4096 : w_h + (k - 2) * 4096) + tid * 8);
    if (tid == 0) {
        if ((uint32_t)__cvta_generic_to_shared(smem_raw) > SB) __trap();
        asm volatile("mbarrier.init.shared.b64 [%0], 1;" :: "r"(SM_BAR) : "memory");
        asm volatile("fence.mbarrier_init.release.cluster;" ::: "memory");
        asm volatile("mbarrier.arrive.expect_tx.shared.b64 _, [%0], %1;" :: "r"(SM_BAR), "r"(NPP * 128) : "memory");
    }
    if (tid < 2 * NP) g_cell[((size_t)(tid >> 1) * NP + cta) * CELLU + (tid & 1)] = make_uint4(0u, 0u, 0u, 0u);
    else if (tid < 2 * NP + 2) reinterpret_cast<uint4*>(g_mail + cta * MAILW)[tid & 1] = make_uint4(0u, 0u, 0u, 0u);
    const int warp = uniform_warp(), wg = warp >> 2;
    __syncthreads();
    TSTAMP(1);
    uint32_t tag;
    {
        uint32_t cell[EPT], rank[EPT];
#pragma unroll
        for (int k = 0; k < 3; k++) {
            const uint32_t dv[4] = {vd[k].x, vd[k].y, vd[k].z, vd[k].w};
            const bool ok = e0 + k * (NT * 4) < N_EDGES;
#pragma unroll
            for (int q = 0; q < 4; q++) {
                cell[k * 4 + q] = dv[q] / NPP;
                rank[k * 4 + q] = atom_inc(ok ? SM_CNT1 + cell[k * 4 + q] * 4 : SM_DUMMY + lane * 4);
            }
        }
        uint32_t rmax = 0;
        tag = (epoch % 0xffffu + 1u) << 16;
        if (tid == 0 && rank[EPT - 1] != 0xffffffffu) {
#pragma unroll
            for (int mt = 0; mt < 6; mt++) tma_load(SM_H + mt * 8192, &maps.h, node0 + mt * 64, SM_BAR);
        }
#pragma unroll
        for (int k = 0; k < 3; k++) {
            const uint32_t dv[4] = {vd[k].x, vd[k].y, vd[k].z, vd[k].w};
            const uint32_t xv[4] = {__byte_perm(vs[k].x, ve[k].x, 0x5410), __byte_perm(vs[k].y, ve[k].x, 0x7610),
                                    __byte_perm(vs[k].z, ve[k].y, 0x5410), __byte_perm(vs[k].w, ve[k].y, 0x7610)};
#pragma unroll
            for (int q = 0; q < 4; q++) {
                const uint32_t p = cell[k * 4 + q], rk = rank[k * 4 + q];
                rmax = max(rmax, rk);
                sts64_lt(rk, CELL, SM_STAGE + (p * CELL + rk) * 8, xv[q], dv[q] + tag - p * NPP);
            }
        }
        if (rmax >= CELL) {
#pragma unroll
            for (int k = 0; k < 3; k++) {
                const uint32_t dv[4] = {vd[k].x, vd[k].y, vd[k].z, vd[k].w};
                const uint32_t xv[4] = {__byte_perm(vs[k].x, ve[k].x, 0x5410), __byte_perm(vs[k].y, ve[k].x, 0x7610),
                                        __byte_perm(vs[k].z, ve[k].y, 0x5410), __byte_perm(vs[k].w, ve[k].y, 0x7610)};
#pragma unroll
                for (int q = 0; q < 4; q++)
                    if (rank[k * 4 + q] >= CELL && rank[k * 4 + q] < (1u << 16))
                        g_ovf[(size_t)cta * CH + atom_inc(F_NOVF)] = make_uint2(xv[q], dv[q]);
            }
        }
    }
    if (tid < NPP) sts64(SM_POS + tid * 8, pv[0] | (pv[1] << 16), pv[2]);
#pragma unroll
    for (int k = 0; k < 4; k++)
        sts128(SM_W + k * 8192 + (tid >> 3) * 128 + (((tid & 7) ^ ((tid >> 3) & 7)) << 4), bmul2(wv[k].x, 0x3F003F00u),
               bmul2(wv[k].y, 0x3F003F00u), bmul2(wv[k].z, 0x3F003F00u), bmul2(wv[k].w, 0x3F003F00u));
    fence_async();
    __syncthreads();
    TSTAMP(2);
    if (tid == 0) g_epoch[cta] = epoch + 1;
    if (cta == 0 && tid < 8)
        g_B[((size_t)(tid >> 2) * BROWS + KILL) * 4 + (tid & 3)] = make_uint4(0xF800F800u, 0xF800F800u, 0xF800F800u, 0xF800F800u);
    if (wg < 2) {
        node_phase(tag, w_e, w_x);
    } else {
        collect_phase(tag);
    }
    TSTAMP(6);
    __syncthreads();
    TSTAMP(7);
    if (tid < NPP) {
        const uint32_t deg = lds32(SM_CNT2 + tid * 4);
        uint32_t skey = 0;
        if (deg > MAXD) sts32(SM_SLOW + atom_inc(F_NSLOW) * 4, tid);
        else skey = (deg + 1) >> 1;
        const uint32_t srank = atom_inc(SM_HIST + skey * 4);
        {
            const uint2 pp = lds64(SM_POS + tid * 8);
            const float x = __uint_as_float(pp.x << 16), y = __uint_as_float(pp.x & 0xffff0000u), z = __uint_as_float(pp.y << 16);
            if (!((x * x + y * y + z * z) * __uint_as_float(lds32(F_WDM)) <= 8192.f)) sts32(F_SLOW, 1u);
        }
        asm volatile("bar.sync 3, %0;" :: "n"(NPP) : "memory");
        const int c = lds32(SM_HIST + (31 - lane) * 4);
        int inc = c;
#pragma unroll
        for (int o = 1; o < 32; o <<= 1) {
            int v = __shfl_up_sync(0xffffffffu, inc, o);
            if (lane >= o) inc += v;
        }
        const int base = __shfl_sync(0xffffffffu, inc - c, 31 - skey);
        sts32(SM_ORD + (base + srank) * 4, (uint32_t)tid | (skey << 16));
        const int gs = (base + srank) & ~7;
        int l = 0;
#pragma unroll
        for (int o = 16; o > 0; o >>= 1)
            if (__shfl_sync(0xffffffffu, inc, l + o - 1) <= gs) l += o;
#pragma unroll 1
        for (int i = deg; i < 2 * (31 - l) + 4; i++) sts32(SM_REC + (tid * CAPN + i) * 4, KILL);
    } else {
        for (int run = tid - NPP; run < NP; run += NT - NPP) {
            const uint32_t v = poll_mail(run, tag);
            sts32(SM_RUN + run * 4, v);
            if (v & 0x8000u) sts32(F_GBIG, 1u);
        }
        TSTAMP_T(15, NPP);
    }
    __syncthreads();
    TSTAMP(8);

    if (lds32(F_GBIG) != 0 && lds32(F_SLOW) == 0) {
        edge_phase(tex0, tex1, out + (size_t)N_NODES * 64 + (size_t)node0 * 3, nown);
        TSTAMP(9);
        __syncthreads();
        const int nslow = lds32(F_NSLOW);
        for (int i = warp; i < nslow; i += NW) slow_node(lds32(SM_SLOW + i * 4), h, pos, w_e, w_x, out);
    } else {
        for (int i = warp; i < nown; i += NW) slow_node(i, h, pos, w_e, w_x, out);
    }
    fence_async();
    __syncthreads();
    TSTAMP(10);

#pragma unroll 1
    for (int mt = wg; mt < 6; mt += 4) {
        if (mt * 64 >= nown) break;
        float acc[32];
        const uint64_t da = mkdesc(SM_H) + mt * 512;
        wg_fence();
        wg_n64<0>(acc, da, mkdesc(SM_W + 16384));
#pragma unroll
        for (int kk = 1; kk < 8; kk++)
            wg_n64<1>(acc, da + (kk < 4 ? 0 : (SM_A - SM_H) / 16) + (kk & 3) * 2, mkdesc(SM_W + 16384 + kk * 2048));
        wg_commit();
        wg_wait0();
        fence_regs(acc);
        const int r = (warp & 3) * 16 + (lane & 7) + ((lane >> 3) & 1) * 8;
#pragma unroll
        for (int q = 0; q < 4; q++) {
            const uint32_t ad = SM_H + mt * 8192 + r * 128 + (((2 * q + (lane >> 4)) ^ (r & 7)) << 4);
            uint32_t hv[4];
            ldsm4(hv, ad);
#pragma unroll
            for (int i = 0; i < 4; i++)
                hv[i] = badd2(hv[i], pack_bf(silu_half(acc[8 * q + 2 * i]), silu_half(acc[8 * q + 2 * i + 1])));
            stsm4(ad, hv[0], hv[1], hv[2], hv[3]);
        }
        fence_async();
        asm volatile("bar.sync %0, 128;" :: "r"(4 + wg) : "memory");
        if ((tid & 127) == 0) {
            tma_store(&maps.out, node0 + mt * 64, SM_H + mt * 8192);
            asm volatile("cp.async.bulk.commit_group;" ::: "memory");
        }
    }
    if ((tid & 127) == 0) asm volatile("cp.async.bulk.wait_group.read 0;" ::: "memory");
    TSTAMP(11);
}

typedef CUresult (*EncodeFn)(CUtensorMap*, CUtensorMapDataType, cuuint32_t, void*, const cuuint64_t*, const cuuint64_t*,
                             const cuuint32_t*, const cuuint32_t*, CUtensorMapInterleave, CUtensorMapSwizzle,
                             CUtensorMapL2promotion, CUtensorMapFloatOOBfill);

void encode_rows(EncodeFn fn, CUtensorMap* m, const void* base, int rows) {
    const cuuint64_t dim[2] = {64, (cuuint64_t)rows};
    const cuuint64_t stride[1] = {128};
    const cuuint32_t box[2] = {64, 64}, es[2] = {1, 1};
    fn(m, CU_TENSOR_MAP_DATA_TYPE_BFLOAT16, 2, const_cast<void*>(base), dim, stride, box, es,
       CU_TENSOR_MAP_INTERLEAVE_NONE, CU_TENSOR_MAP_SWIZZLE_128B, CU_TENSOR_MAP_L2_PROMOTION_NONE,
       CU_TENSOR_MAP_FLOAT_OOB_FILL_NONE);
}

}

extern "C" void kernel_launch(void* const* d_in, const int* in_sizes, int n_in, void* d_out, int out_size) {
    (void)in_sizes; (void)n_in; (void)out_size;
    static bool init_done = false;
    static cudaTextureObject_t tex[2] = {0, 0};
    static EncodeFn encode = nullptr;
    if (!init_done) {
        cudaFuncSetAttribute(egnn_kernel, cudaFuncAttributeMaxDynamicSharedMemorySize, SM_END);
        void* pB = nullptr;
        cudaGetSymbolAddress(&pB, g_B);
        for (int i = 0; i < 2; i++) {
            cudaResourceDesc rd = {};
            rd.resType = cudaResourceTypeLinear;
            rd.res.linear.devPtr = (char*)pB + (size_t)i * BROWS * 64;
            rd.res.linear.desc = cudaCreateChannelDesc(32, 32, 32, 32, cudaChannelFormatKindUnsigned);
            rd.res.linear.sizeInBytes = (size_t)BROWS * 64;
            cudaTextureDesc td = {};
            td.readMode = cudaReadModeElementType;
            cudaCreateTextureObject(&tex[i], &rd, &td, nullptr);
        }
        cudaDriverEntryPointQueryResult qr;
        void* fn = nullptr;
        cudaGetDriverEntryPoint("cuTensorMapEncodeTiled", &fn, cudaEnableDefault, &qr);
        encode = (EncodeFn)fn;
        init_done = true;
    }
    Maps maps;
    encode_rows(encode, &maps.h, d_in[0], N_NODES);
    encode_rows(encode, &maps.out, d_out, N_NODES);
    egnn_kernel<<<NP, NT, SM_END>>>(
        (const __nv_bfloat16*)d_in[0], (const __nv_bfloat16*)d_in[1], (const __nv_bfloat16*)d_in[2],
        (const int*)d_in[3], (const int*)d_in[4], (const __nv_bfloat16*)d_in[5], (const __nv_bfloat16*)d_in[6],
        (const __nv_bfloat16*)d_in[7], (__nv_bfloat16*)d_out, tex[0], tex[1], maps);
}
```

```cpp
#include <cuda.h>
#include <cuda_runtime.h>
#include <cuda_bf16.h>
#include <cuda_fp16.h>
#include <stdint.h>

#define H1TILES 3
#define PRED_ATOM 0
#define EARLY 2
#define RELAXED 1

namespace {

constexpr int N_NODES = 50000;
constexpr int N_EDGES = 800000;
constexpr int NT = 768;
constexpr int NW = NT / 32;
constexpr int NPP = 384;
constexpr int NP = (N_NODES + NPP - 1) / NPP;
constexpr int EPT = 8;
constexpr int CH = NT * EPT;
constexpr int CELLU = 28;
constexpr int CELL = 3 * CELLU;
constexpr int CAPN = 46;
constexpr int MAXD = CAPN;
constexpr int MAILW = 32;
constexpr uint32_t KILL = NP * NPP;
constexpr int BROWS = NP * NPP + 1;
constexpr int NCW = 12;
constexpr int RPW = (NP + NCW - 1) / NCW;
static_assert(NP * CH >= N_EDGES, "chunks must cover the edge list");
static_assert(N_EDGES % 4 == 0 && KILL < 65536, "shape assumptions");
static_assert(NP <= 144 && RPW <= 18, "loop bounds");

constexpr uint32_t SB = 2048;
constexpr uint32_t SM_H = SB;
constexpr uint32_t SM_W = SM_H + NPP * 128;
constexpr uint32_t SM_A = SM_W + 4 * 8192;
constexpr uint32_t SM_REC = SM_A + NPP * 128;
constexpr uint32_t SM_STAGE = SM_A;
constexpr uint32_t SM_POS = SM_REC + NPP * CAPN * 4;
constexpr uint32_t SM_CNT1 = SM_POS + NPP * 8;
constexpr uint32_t SM_CNT2 = SM_CNT1 + 160 * 4;
constexpr uint32_t SM_HIST = SM_CNT2 + NPP * 4;
constexpr uint32_t SM_FLAG = SM_HIST + 32 * 4;
constexpr uint32_t SM_DUMMY = SM_FLAG + 64;
constexpr uint32_t SM_RUN = SM_DUMMY + 128;
constexpr uint32_t SM_ORD = SM_RUN + 160 * 4;
constexpr uint32_t SM_BAR = SM_ORD + NPP * 4;
constexpr uint32_t SM_CONST = SM_BAR + 48;
constexpr uint32_t SM_END = SM_CONST + 5 * 512;
static_assert((RPW * NCW * CELLU + 4) * 16 <= NPP * 128 + NPP * CAPN * 4, "staging must fit");
static_assert(SM_A % 1024 == 0 && SM_W % 1024 == 0 && SM_REC % 16 == 0 && SM_CONST % 16 == 0 && SM_CNT1 % 16 == 0, "alignment");
constexpr uint32_t SM_META = SM_STAGE + (RPW * NCW * CELLU + 4) * 16;
constexpr uint32_t SM_ED = SM_H, SM_ES = SM_H + CH * 4, SM_EA = SM_W + 16384;
constexpr uint32_t SM_RX = SM_POS - 128, SM_RW = SM_RX - 130 * 128, SM_RP = SM_RW - NPP * 6, SM_RE = SM_RP - 16;
static_assert(SM_RE >= SM_META + 2 * NT * 16 && 2 * NT * 4 >= RPW * NCW * CELLU + 4 && SM_RE % 16 == 0, "temporaries must not overlap the staging");
constexpr uint32_t F_BIG = SM_FLAG, F_GBIG = SM_FLAG + 4, F_SLOW = SM_FLAG + 8,
                   F_WDM = SM_FLAG + 16, F_NOVF = SM_FLAG + 20;

__device__ uint4 g_cell[(NP * NP + 128) * CELLU];
__device__ uint2 g_ovf[NP * CH];
__device__ __align__(1024) uint4 g_B[BROWS * 8];
__device__ uint32_t g_mail[NP * MAILW];
__device__ uint4 g_epoch[NP];
#define TSTAMP_T(i, th)
#define TSTAMP(i) TSTAMP_T(i, 0)
#define TSTAMP_X(i, op)

__device__ __forceinline__ void hmma16_h(uint32_t& d0, uint32_t& d1, uint32_t a0, uint32_t a1, uint32_t a2, uint32_t a3,
                                         uint32_t b0, uint32_t b1, uint32_t c0, uint32_t c1) {
    asm("mma.sync.aligned.m16n8k16.row.col.f16.f16.f16.f16 {%0,%1}, {%2,%3,%4,%5}, {%6,%7}, {%8,%9};"
        : "=r"(d0), "=r"(d1) : "r"(a0), "r"(a1), "r"(a2), "r"(a3), "r"(b0), "r"(b1), "r"(c0), "r"(c1));
}
__device__ __forceinline__ void hmma8_h(uint32_t& d0, uint32_t& d1, uint32_t a0, uint32_t a1, uint32_t b0) {
    asm("mma.sync.aligned.m16n8k8.row.col.f16.f16.f16.f16 {%0,%1}, {%2,%3}, {%4}, {%0,%1};"
        : "+r"(d0), "+r"(d1) : "r"(a0), "r"(a1), "r"(b0));
}
__device__ __forceinline__ void hmma16_f(float (&d)[4], uint32_t a0, uint32_t a1, uint32_t a2, uint32_t a3,
                                         uint32_t b0, uint32_t b1) {
    asm("mma.sync.aligned.m16n8k16.row.col.f32.f16.f16.f32 {%0,%1,%2,%3}, {%4,%5,%6,%7}, {%8,%9}, {%0,%1,%2,%3};"
        : "+f"(d[0]), "+f"(d[1]), "+f"(d[2]), "+f"(d[3])
        : "r"(a0), "r"(a1), "r"(a2), "r"(a3), "r"(b0), "r"(b1));
}
__host__ __device__ constexpr uint64_t mkdesc(uint32_t addr) {
    return (uint64_t)((addr & 0x3FFFF) >> 4) | ((uint64_t)1 << 16) | ((uint64_t)64 << 32) | ((uint64_t)1 << 62);
}
__device__ __forceinline__ void wg_fence() { asm volatile("wgmma.fence.sync.aligned;" ::: "memory"); }
__device__ __forceinline__ void wg_commit() { asm volatile("wgmma.commit_group.sync.aligned;" ::: "memory"); }
__device__ __forceinline__ void wg_wait0() { asm volatile("wgmma.wait_group.sync.aligned 0;" ::: "memory"); }
template <int ACC>
__device__ __forceinline__ void wg_n64(float (&d)[32], uint64_t da, uint64_t db) {
    asm volatile("{.reg .pred p; setp.ne.b32 p, %34, 0;\n"
        "wgmma.mma_async.sync.aligned.m64n64k16.f32.bf16.bf16 "
        "{%0,%1,%2,%3,%4,%5,%6,%7,%8,%9,%10,%11,%12,%13,%14,%15,%16,%17,%18,%19,%20,%21,%22,%23,%24,%25,%26,%27,%28,%29,%30,%31},"
        " %32, %33, p, 1, 1, 0, 1;}"
        : "+f"(d[0]), "+f"(d[1]), "+f"(d[2]), "+f"(d[3]), "+f"(d[4]), "+f"(d[5]), "+f"(d[6]), "+f"(d[7]),
          "+f"(d[8]), "+f"(d[9]), "+f"(d[10]), "+f"(d[11]), "+f"(d[12]), "+f"(d[13]), "+f"(d[14]), "+f"(d[15]),
          "+f"(d[16]), "+f"(d[17]), "+f"(d[18]), "+f"(d[19]), "+f"(d[20]), "+f"(d[21]), "+f"(d[22]), "+f"(d[23]),
          "+f"(d[24]), "+f"(d[25]), "+f"(d[26]), "+f"(d[27]), "+f"(d[28]), "+f"(d[29]), "+f"(d[30]), "+f"(d[31])
        : "l"(da), "l"(db), "n"(ACC));
}
template <int ACC>
__device__ __forceinline__ void wg_n64r(float (&d)[32], const uint32_t (&a)[4], uint64_t db) {
    asm volatile("{.reg .pred p; setp.ne.b32 p, %37, 0;\n"
        "wgmma.mma_async.sync.aligned.m64n64k16.f32.bf16.bf16 "
        "{%0,%1,%2,%3,%4,%5,%6,%7,%8,%9,%10,%11,%12,%13,%14,%15,%16,%17,%18,%19,%20,%21,%22,%23,%24,%25,%26,%27,%28,%29,%30,%31},"
        " {%32,%33,%34,%35}, %36, p, 1, 1, 1;}"
        : "+f"(d[0]), "+f"(d[1]), "+f"(d[2]), "+f"(d[3]), "+f"(d[4]), "+f"(d[5]), "+f"(d[6]), "+f"(d[7]),
          "+f"(d[8]), "+f"(d[9]), "+f"(d[10]), "+f"(d[11]), "+f"(d[12]), "+f"(d[13]), "+f"(d[14]), "+f"(d[15]),
          "+f"(d[16]), "+f"(d[17]), "+f"(d[18]), "+f"(d[19]), "+f"(d[20]), "+f"(d[21]), "+f"(d[22]), "+f"(d[23]),
          "+f"(d[24]), "+f"(d[25]), "+f"(d[26]), "+f"(d[27]), "+f"(d[28]), "+f"(d[29]), "+f"(d[30]), "+f"(d[31])
        : "r"(a[0]), "r"(a[1]), "r"(a[2]), "r"(a[3]), "l"(db), "n"(ACC));
}
__device__ __forceinline__ void fence_regs(float (&d)[32]) {
#pragma unroll
    for (int i = 0; i < 32; i++) asm volatile("" : "+f"(d[i]) :: "memory");
}
__device__ __forceinline__ void fence_async() { asm volatile("fence.proxy.async.shared::cta;" ::: "memory"); }
__device__ __forceinline__ void stsm4(uint32_t addr, uint32_t r0, uint32_t r1, uint32_t r2, uint32_t r3) {
    asm volatile("stmatrix.sync.aligned.m8n8.x4.shared.b16 [%0], {%1,%2,%3,%4};"
                 :: "r"(addr), "r"(r0), "r"(r1), "r"(r2), "r"(r3) : "memory");
}
__device__ __forceinline__ void ldsm4(uint32_t (&r)[4], uint32_t addr) {
    asm volatile("ldmatrix.sync.aligned.m8n8.x4.shared.b16 {%0,%1,%2,%3}, [%4];"
                 : "=r"(r[0]), "=r"(r[1]), "=r"(r[2]), "=r"(r[3]) : "r"(addr) : "memory");
}
__device__ __forceinline__ uint32_t pack_bf(float lo, float hi) {
    uint32_t d;
    asm("cvt.rn.bf16x2.f32 %0, %1, %2;" : "=r"(d) : "f"(hi), "f"(lo));
    return d;
}
__device__ __forceinline__ uint32_t pack_h(float lo, float hi) {
    uint32_t d;
    asm("cvt.rn.f16x2.f32 %0, %1, %2;" : "=r"(d) : "f"(hi), "f"(lo));
    return d;
}
__device__ __forceinline__ uint32_t bmul2(uint32_t a, uint32_t b) {
    uint32_t d;
    asm("mul.rn.bf16x2 %0, %1, %2;" : "=r"(d) : "r"(a), "r"(b));
    return d;
}
__device__ __forceinline__ uint32_t badd2(uint32_t a, uint32_t b) {
    uint32_t d;
    asm("add.rn.bf16x2 %0, %1, %2;" : "=r"(d) : "r"(a), "r"(b));
    return d;
}
__device__ __forceinline__ uint32_t bsub2(uint32_t a, uint32_t b) {
    uint32_t d;
    asm("sub.rn.bf16x2 %0, %1, %2;" : "=r"(d) : "r"(a), "r"(b));
    return d;
}
__device__ __forceinline__ uint32_t hadd2(uint32_t a, uint32_t b) {
    uint32_t d;
    asm("add.rn.f16x2 %0, %1, %2;" : "=r"(d) : "r"(a), "r"(b));
    return d;
}
__device__ __forceinline__ uint32_t habsmax2(uint32_t a, uint32_t b) {
    uint32_t d;
    asm("max.NaN.xorsign.abs.f16x2 %0, %1, %2;" : "=r"(d) : "r"(a), "r"(b));
    return d;
}
__device__ __forceinline__ float silu_half(float x) {
    float t;
    asm("tanh.approx.f32 %0, %1;" : "=f"(t) : "f"(x));
    return fmaf(x, t, x);
}
__device__ __forceinline__ uint32_t silu_half2(uint32_t x) {
    uint32_t t, m;
    asm("tanh.approx.f16x2 %0, %1;" : "=r"(t) : "r"(x));
    asm("fma.rn.f16x2 %0, %1, %2, %1;" : "=r"(m) : "r"(x), "r"(t));
    return m;
}
__device__ __forceinline__ uint4 ldg_relaxed(const void* p) {
    uint4 v;
    asm volatile("ld.relaxed.gpu.global.v4.u32 {%0,%1,%2,%3}, [%4];"
                 : "=r"(v.x), "=r"(v.y), "=r"(v.z), "=r"(v.w) : "l"(p) : "memory");
    return v;
}
__device__ __forceinline__ uint4 ldg_cg(const void* p) {
    uint4 v;
    asm volatile("ld.global.L1::no_allocate.v4.u32 {%0,%1,%2,%3}, [%4];"
                 : "=r"(v.x), "=r"(v.y), "=r"(v.z), "=r"(v.w) : "l"(p) : "memory");
    return v;
}
template <int OFF, int BIT>
__device__ __forceinline__ void ldg_bit(uint4& v, const void* p, uint32_t m) {
    asm volatile("{.reg .pred q; .reg .b32 t; and.b32 t, %5, %7; setp.ne.u32 q, t, 0;\n"
                 "@q ld.global.L1::no_allocate.v4.u32 {%0,%1,%2,%3}, [%4+%6];}"
                 : "+r"(v.x), "+r"(v.y), "+r"(v.z), "+r"(v.w) : "l"(p), "r"(m), "n"(OFF), "n"(BIT) : "memory");
}
template <int OFF>
__device__ __forceinline__ void stg_nz(void* p, const uint4& v) {
    asm volatile("{.reg .pred q; setp.ne.u32 q, %4, 0; @q st.global.v4.u32 [%0+%5], {%1,%2,%3,%4};}"
                 :: "l"(p), "r"(v.x), "r"(v.y), "r"(v.z), "r"(v.w), "n"(OFF) : "memory");
}
template <int V> struct IC { static constexpr int v = V; };
template <int N, class F>
__device__ __forceinline__ void static_for(F&& f) {
    if constexpr (N > 0) { static_for<N - 1>(f); f(IC<N - 1>{}); }
}
__device__ __forceinline__ uint4 ldg_nc(const void* p) {
    uint4 v;
    asm volatile("ld.global.nc.L1::no_allocate.v4.u32 {%0,%1,%2,%3}, [%4];"
                 : "=r"(v.x), "=r"(v.y), "=r"(v.z), "=r"(v.w) : "l"(p));
    return v;
}
__device__ __forceinline__ uint2 ldg_nc2(const void* p) {
    uint2 v;
    asm volatile("ld.global.nc.L1::no_allocate.v2.u32 {%0,%1}, [%2];" : "=r"(v.x), "=r"(v.y) : "l"(p));
    return v;
}
__device__ __forceinline__ uint2 ldg_cg2(const void* p) {
    uint2 v;
    asm volatile("ld.global.L1::no_allocate.v2.u32 {%0,%1}, [%2];" : "=r"(v.x), "=r"(v.y) : "l"(p) : "memory");
    return v;
}
__device__ __forceinline__ uint32_t bf16_bits(const __nv_bfloat16* p) {
    return (uint32_t)__ldg(reinterpret_cast<const unsigned short*>(p));
}
__device__ __forceinline__ float bf16_val(const __nv_bfloat16* p) { return __uint_as_float(bf16_bits(p) << 16); }
__device__ __forceinline__ uint4 tex_row(cudaTextureObject_t tex, uint32_t i) {
    uint4 v;
    asm volatile("tex.1d.v4.u32.s32 {%0,%1,%2,%3}, [%4, {%5}];"
                 : "=r"(v.x), "=r"(v.y), "=r"(v.z), "=r"(v.w) : "l"(tex), "r"(i));
    return v;
}
__device__ __forceinline__ uint32_t lds16(uint32_t addr) {
    uint32_t v;
    asm volatile("ld.shared.u16 %0, [%1];" : "=r"(v) : "r"(addr) : "memory");
    return v;
}
__device__ __forceinline__ uint32_t lds32(uint32_t addr) {
    uint32_t v;
    asm volatile("ld.shared.u32 %0, [%1];" : "=r"(v) : "r"(addr) : "memory");
    return v;
}
__device__ __forceinline__ uint2 lds64(uint32_t addr) {
    uint2 v;
    asm volatile("ld.shared.v2.u32 {%0,%1}, [%2];" : "=r"(v.x), "=r"(v.y) : "r"(addr) : "memory");
    return v;
}
__device__ __forceinline__ uint4 lds128(uint32_t addr) {
    uint4 v;
    asm volatile("ld.shared.v4.u32 {%0,%1,%2,%3}, [%4];" : "=r"(v.x), "=r"(v.y), "=r"(v.z), "=r"(v.w) : "r"(addr) : "memory");
    return v;
}
__device__ __forceinline__ void sts32(uint32_t addr, uint32_t v) {
    asm volatile("st.shared.u32 [%0], %1;" :: "r"(addr), "r"(v) : "memory");
}
__device__ __forceinline__ void sts64(uint32_t addr, uint32_t a, uint32_t b) {
    asm volatile("st.shared.v2.u32 [%0], {%1,%2};" :: "r"(addr), "r"(a), "r"(b) : "memory");
}
__device__ __forceinline__ void sts128(uint32_t addr, uint32_t a, uint32_t b, uint32_t c, uint32_t d) {
    asm volatile("st.shared.v4.u32 [%0], {%1,%2,%3,%4};" :: "r"(addr), "r"(a), "r"(b), "r"(c), "r"(d) : "memory");
}
__device__ __forceinline__ uint32_t atom_inc(uint32_t addr) {
    uint32_t r;
    asm volatile("atom.shared.add.u32 %0, [%1], 1;" : "=r"(r) : "r"(addr) : "memory");
    return r;
}
__device__ __forceinline__ uint32_t atom_inc_nz(uint32_t f, uint32_t addr) {
    uint32_t r;
    asm volatile("{.reg .pred q; setp.ne.u32 q, %2, 0; @q atom.shared.inc.u32 %0, [%1], 0xffffffff;}" : "=r"(r) : "r"(addr), "r"(f) : "memory");
    return r;
}
__device__ __forceinline__ void sts32_nz_lt(uint32_t f, uint32_t a, uint32_t b, uint32_t addr, uint32_t v) {
    asm volatile("{.reg .pred q, p; setp.ne.u32 p, %4, 0; setp.lt.and.u32 q, %2, %3, p; @q st.shared.u32 [%0], %1;}"
                 :: "r"(addr), "r"(v), "r"(a), "r"(b), "r"(f) : "memory");
}
__device__ __forceinline__ void red_or(uint32_t addr, uint32_t v) {
    asm volatile("red.shared.or.b32 [%0], %1;" :: "r"(addr), "r"(v) : "memory");
}
__device__ __forceinline__ void sts32_lt(uint32_t a, uint32_t b, uint32_t addr, uint32_t v) {
    asm volatile("{.reg .pred q; setp.lt.u32 q, %2, %3; @q st.shared.u32 [%0], %1;}"
                 :: "r"(addr), "r"(v), "r"(a), "r"(b) : "memory");
}
__device__ __forceinline__ void sts64_lt(uint32_t a, uint32_t b, uint32_t addr, uint32_t x, uint32_t y) {
    asm volatile("{.reg .pred q; setp.lt.u32 q, %3, %4; @q st.shared.v2.u32 [%0], {%1,%2};}"
                 :: "r"(addr), "r"(x), "r"(y), "r"(a), "r"(b) : "memory");
}
__device__ __forceinline__ uint32_t and3(uint32_t a, uint32_t b, uint32_t c) {
    uint32_t d;
    asm("lop3.b32 %0, %1, %2, %3, 0x80;" : "=r"(d) : "r"(a), "r"(b), "r"(c));
    return d;
}
template <uint32_t M>
__device__ __forceinline__ uint32_t and_or(uint32_t a, uint32_t b) {
    uint32_t d;
    asm("lop3.b32 %0, %1, %2, %3, 0xEC;" : "=r"(d) : "r"(a), "r"(b), "n"(M));
    return d;
}
template <uint32_t M>
__device__ __forceinline__ uint32_t bitsel(uint32_t a, uint32_t b) {
    uint32_t d;
    asm("lop3.b32 %0, %1, %2, %3, 0xE4;" : "=r"(d) : "r"(a), "r"(b), "n"(M));
    return d;
}
__device__ __forceinline__ uint32_t extract16(const uint4& r) {
    const uint32_t u = bitsel<0x00030003u>(r.x, r.y << 2);
    const uint32_t v = bitsel<0x00030003u>(r.z, r.w << 2);
    const uint32_t w = bitsel<0x000F000Fu>(u, v << 4);
    return __byte_perm(w, 0u, 0x2044);
}
__device__ __forceinline__ float bfr(float x) { return __bfloat162float(__float2bfloat16(x)); }
__device__ __forceinline__ void mbar_wait(uint32_t bar) {
    uint32_t done = 0;
    int spin = 0;
    while (!done) {
        asm volatile("{.reg .pred p; mbarrier.try_wait.parity.shared.b64 p, [%1], 0; selp.u32 %0, 1, 0, p;}"
                     : "=r"(done) : "r"(bar) : "memory");
        if (++spin > (1 << 24)) __trap();
    }
}
__device__ __forceinline__ void tma_load(uint32_t dst, const CUtensorMap* tm, int row, uint32_t bar) {
    asm volatile("cp.async.bulk.tensor.2d.shared::cluster.global.mbarrier::complete_tx::bytes [%0], [%1, {%3, %4}], [%2];"
                 :: "r"(dst), "l"(tm), "r"(bar), "r"(0), "r"(row) : "memory");
}
__device__ __forceinline__ void bulk_load(uint32_t dst, const void* src, uint32_t bytes, uint32_t bar) {
    asm volatile("cp.async.bulk.shared::cluster.global.mbarrier::complete_tx::bytes [%0], [%1], %2, [%3];"
                 :: "r"(dst), "l"(src), "r"(bytes), "r"(bar) : "memory");
}
__device__ __forceinline__ uint32_t poll_mail(int run, uint32_t tag) {
    uint32_t v;
    int spin = 0;
    while (true) {
        asm volatile("ld.acquire.gpu.global.u32 %0, [%1];" : "=r"(v) : "l"(&g_mail[run * MAILW]) : "memory");
        if ((v ^ tag) < 0x10000u) break;
        if (++spin > (1 << 24)) __trap();
    }
    return v;
}
__device__ __forceinline__ void place_rec(uint32_t x, uint32_t ln) {
    const uint32_t rk = atom_inc(SM_CNT2 + ln * 4);
    sts32_lt(rk, CAPN, SM_REC + (ln * CAPN + rk) * 4, x);
}
__device__ __forceinline__ int uniform_warp() { return __shfl_sync(0xffffffffu, threadIdx.x >> 5, 0); }

__device__ __noinline__ void slow_node(int ln, const __nv_bfloat16* h, const __nv_bfloat16* pos,
                                       const __nv_bfloat16* w_e, const __nv_bfloat16* w_x, __nv_bfloat16* out) {
    const int lane = threadIdx.x & 31, c = 2 * lane;
    const int node = blockIdx.x * NPP + ln;
    float a0 = 0.f, a1 = 0.f;
#pragma unroll 4
    for (int k = 0; k < 64; k++) {
        const float hv = bf16_val(h + (size_t)node * 64 + k);
        a0 = fmaf(hv, bf16_val(w_e + k * 64 + c), a0);
        a1 = fmaf(hv, bf16_val(w_e + k * 64 + c + 1), a1);
    }
    const float wd0 = bf16_val(w_e + 128 * 64 + c), wd1 = bf16_val(w_e + 128 * 64 + c + 1);
    const float wa0 = bf16_val(w_e + 129 * 64 + c), wa1 = bf16_val(w_e + 129 * 64 + c + 1);
    const float wx0 = bf16_val(w_x + c), wx1 = bf16_val(w_x + c + 1);
    const float px = bf16_val(pos + (size_t)node * 3), py = bf16_val(pos + (size_t)node * 3 + 1),
                pz = bf16_val(pos + (size_t)node * 3 + 2);
    float m0 = 0.f, m1 = 0.f, ux = 0.f, uy = 0.f, uz = 0.f;
    for (int run = 0; run < NP; run++) {
        const int novf = lds32(SM_RUN + run * 4) & 0x1fff;
        const uint32_t* cell = reinterpret_cast<const uint32_t*>(g_cell + ((size_t)blockIdx.x * NP + run) * CELLU);
        const int ncell = min((int)(__ldcg(cell) & 0xffffu), CELL);
        for (int i0 = 0; i0 < 96 + novf; i0 += 32) {
            const int i = i0 + lane;
            uint2 rec = make_uint2(0u, 0u);
            bool hit = false;
            if (i < ncell) {
                const int u = i / 3, j = i - 3 * u;
                rec.x = __ldcg(cell + 4 * u + j);
                hit = ((__ldcg(cell + 4 * u + 3) >> (9 * j)) & 511u) == (uint32_t)ln + 1;
            } else if (i >= 96 && i - 96 < novf) {
                rec = __ldcg(g_ovf + (size_t)run * CH + i - 96);
                hit = rec.y == (uint32_t)node;
            }
            uint32_t bal = __ballot_sync(0xffffffffu, hit);
            while (bal) {
                const int l = __ffs(bal) - 1;
                bal &= bal - 1;
                const uint32_t rx = __shfl_sync(0xffffffffu, rec.x, l);
                const int s = rx & 0xffff;
                const float ea = __uint_as_float(rx & 0xffff0000u);
                float b0 = a0, b1 = a1;
#pragma unroll 8
                for (int k = 0; k < 64; k++) {
                    const float hv = bf16_val(h + (size_t)s * 64 + k);
                    b0 = fmaf(hv, bf16_val(w_e + (64 + k) * 64 + c), b0);
                    b1 = fmaf(hv, bf16_val(w_e + (64 + k) * 64 + c + 1), b1);
                }
                const float dx = bfr(px - bf16_val(pos + (size_t)s * 3)), dy = bfr(py - bf16_val(pos + (size_t)s * 3 + 1)),
                            dz = bfr(pz - bf16_val(pos + (size_t)s * 3 + 2));
                const float d2 = dx * dx + dy * dy + dz * dz;
                b0 = fmaf(ea, wa0, fmaf(d2, wd0, b0));
                b1 = fmaf(ea, wa1, fmaf(d2, wd1, b1));
                const float s0 = b0 / (1.f + __expf(-b0)), s1 = b1 / (1.f + __expf(-b1));
                m0 += s0; m1 += s1;
                float cs = s0 * wx0 + s1 * wx1;
#pragma unroll
                for (int o = 16; o > 0; o >>= 1) cs += __shfl_xor_sync(0xffffffffu, cs, o);
                ux = fmaf(dx, cs, ux); uy = fmaf(dy, cs, uy); uz = fmaf(dz, cs, uz);
            }
        }
    }
    sts32(SM_A + ln * 128 + (((lane >> 2) ^ (ln & 7)) << 4) + (lane & 3) * 4, pack_bf(m0, m1));
    if (lane == 0) {
        __nv_bfloat16* pp = out + (size_t)N_NODES * 64 + (size_t)node * 3;
        pp[0] = __float2bfloat16(px + ux); pp[1] = __float2bfloat16(py + uy); pp[2] = __float2bfloat16(pz + uz);
    }
}
__device__ __noinline__ void collect_overflow(int run, uint32_t tag) {
    const int novf = poll_mail(run, tag) & 0x1fff;
    for (int i = threadIdx.x & 31; i < novf; i += 32) {
        const uint2 r = __ldcg(g_ovf + (size_t)run * CH + i);
        const uint32_t ln = r.y - blockIdx.x * NPP;
        if (ln < (uint32_t)NPP) place_rec(r.x, ln);
    }
    __syncwarp();
}

__device__ __forceinline__ void const_phase() {
    auto val = [](uint32_t ad) { return __uint_as_float(lds16(ad) << 16); };
    constexpr uint32_t WD = SM_RW + 128 * 128, WA = WD + 128;
    const int lane = threadIdx.x & 31, g = lane >> 2, t = lane & 3;
    const float wd0 = fabsf(val(WD + lane * 2)), wd1 = fabsf(val(WD + 64 + lane * 2));
    const float wa0 = fabsf(val(WA + lane * 2)), wa1 = fabsf(val(WA + 64 + lane * 2));
    float wgf[8], wxf[8];
#pragma unroll
    for (int i = 0; i < 8; i++) wgf[i] = 0.5f * val((t < 3 ? WD : WA) + g * 2 + 16 * i);
    float wxm = 0.f;
#pragma unroll
    for (int i = 0; i < 8; i++) {
        wxf[i] = val(SM_RX + (16 * (i >> 1) + 8 * (g & 1) + 2 * t + (i & 1)) * 2);
        wxm = fmaxf(wxm, fabsf(wxf[i]));
    }
    const float wdm = __uint_as_float(__reduce_max_sync(0xffffffffu, __float_as_uint(fmaxf(wd0, wd1))));
    const float wam = __uint_as_float(__reduce_max_sync(0xffffffffu, __float_as_uint(fmaxf(wa0, wa1))));
    const uint32_t wxe = min(max(__reduce_max_sync(0xffffffffu, __float_as_uint(wxm)) >> 23, 2u), 252u);
    const float sc = __uint_as_float((254u - wxe) << 23);
    if (!(wdm == 0.f || (wdm >= 1.953125e-3f && wdm <= 32.f)) || !(wam == 0.f || (wam >= 1.953125e-3f && wam <= 32.f)))
        sts32(F_SLOW, 1u);
    sts32(F_WDM, __float_as_uint(wdm));
    const uint32_t ad = SM_CONST + lane * 16;
    sts128(ad, pack_h(wgf[0], wgf[1]), pack_h(wgf[2], wgf[3]), pack_h(wgf[4], wgf[5]), pack_h(wgf[6], wgf[7]));
    sts128(ad + 512, pack_h(sc * wxf[0], sc * wxf[1]), pack_h(sc * wxf[2], sc * wxf[3]),
           pack_h(sc * wxf[4], sc * wxf[5]), pack_h(sc * wxf[6], sc * wxf[7]));
    sts128(ad + 1536, 0u, 0u, ((g >> 1) == t) ? 0x3f800000u : 0u, 0u);
    sts128(ad + 2048, ((g >> 1) == t) ? (0x3C00u << (16 * (g & 1))) : 0u, ((g >> 1) == t) ? 0x3f800000u : 0u,
           t == 3 ? 0xffff0000u : 0u, wxe << 23);
}

__device__ __forceinline__ void node_phase(uint32_t tag) {
    const int lane = threadIdx.x & 31, g = lane >> 2, t = lane & 3;
    const int warp = uniform_warp(), wg = warp >> 2;
    const int row = wg * 64 + (warp & 3) * 16 + g;
    float acc[32];
    auto gemm = [&](int j, uint32_t w) {
        const uint64_t da = mkdesc(SM_H) + (wg + 3 * j) * 512;
        wg_fence();
        wg_n64<0>(acc, da, mkdesc(w));
#pragma unroll
        for (int kk = 1; kk < 4; kk++) wg_n64<1>(acc, da + kk * 2, mkdesc(w + kk * 2048));
        wg_commit();
        wg_wait0();
        fence_regs(acc);
    };
    uint32_t c[4];
#pragma unroll
    for (int i = 0; i < 4; i++)
        c[i] = __byte_perm(lds16(SM_POS + row * 8 + 2 * t + (i >> 1) * 1536 + (i & 1) * 64), 0u, 0x4140);
#pragma unroll
    for (int j = 0; j < 2; j++) {
        mbar_wait(j == 0 ? SM_BAR + 32 : SM_BAR);
        TSTAMP(16 + j);
        gemm(j, SM_W + 8192);
        if (j == 0) {
            if (fmaxf(fabsf(acc[0]), fabsf(acc[31])) >= 9.765625e-4f) sts32(F_BIG, 0x8000u);
            asm volatile("bar.sync 8, %0;" :: "n"(NT) : "memory");
        }
#pragma unroll
        for (int hf = 0; hf < 2; hf++) {
            const float* a = acc + 2 * hf;
            const uint32_t ad = SM_A + row * 128 + t * 16 + j * 24576 + hf * 1024, cc = c[2 * j + hf];
            sts128(ad, bitsel<0x00030003u>(cc, pack_h(a[0], a[1])), bitsel<0x00030003u>(cc >> 2, pack_h(a[4], a[5])),
                   bitsel<0x00030003u>(cc >> 4, pack_h(a[8], a[9])), bitsel<0x00030003u>(cc >> 6, pack_h(a[12], a[13])));
            sts128(ad + 64, pack_h(a[16], a[17]), pack_h(a[20], a[21]), pack_h(a[24], a[25]), pack_h(a[28], a[29]));
        }
    }
    fence_async();
    auto store_B = [&](int part, int parts) {
        asm volatile("cp.async.bulk.global.shared::cta.bulk_group [%0], [%1], %2;"
                     :: "l"(g_B + ((size_t)blockIdx.x * NPP + part * 64) * 8), "r"(SM_A + part * 8192), "r"(parts * 8192) : "memory");
        asm volatile("cp.async.bulk.commit_group;" ::: "memory");
    };
    if (warp != 0) {
        asm volatile("bar.arrive 1, 384;" ::: "memory");
    } else {
        asm volatile("bar.sync 1, 384;" ::: "memory");
        if (lane == 0) store_B(0, EARLY);
        __syncwarp();
    }
    TSTAMP(4);
    uint32_t aw[2][16], amax;
#pragma unroll
    for (int j = 0; j < 2; j++) {
        gemm(j, SM_W);
#pragma unroll
        for (int i = 0; i < 16; i++) {
            const int e = i >> 2, q = i & 3;
            aw[j][i] = pack_h(acc[8 * q + e], acc[8 * q + 4 + e]);
            amax = i + j == 0 ? aw[j][i] : habsmax2(amax, aw[j][i]);
        }
    }
    if ((amax & 0x7fffu) > 0x7000u || (amax & 0x7fff0000u) > 0x70000000u) sts32(F_SLOW, 1u);
    if (warp == 0) {
        asm volatile("bar.sync 10, 416;" ::: "memory");
        TSTAMP(13);
        if (lane == 0) {
            store_B(EARLY, 6 - EARLY);
            asm volatile("cp.async.bulk.wait_group 0;" ::: "memory");
            asm volatile("st.relaxed.gpu.global.u32 [%0], %1;"
                         :: "l"(&g_mail[blockIdx.x * MAILW]), "r"(tag | lds32(F_BIG) | lds32(F_NOVF)) : "memory");
        }
        __syncwarp();
        TSTAMP(18);
        asm volatile("bar.arrive 2, 384;" ::: "memory");
    } else {
        asm volatile("bar.sync 2, 384;" ::: "memory");
    }
#pragma unroll
    for (int j = 0; j < 2; j++) {
#pragma unroll
        for (int e = 0; e < 4; e++)
            sts128(SM_A + row * 128 + j * 24576 + (e >> 1) * 1024 + (((2 * t + (e & 1)) ^ g) << 4),
                   aw[j][4 * e], aw[j][4 * e + 1], aw[j][4 * e + 2], aw[j][4 * e + 3]);
    }
}

__device__ __forceinline__ void collect_phase(uint32_t tag) {
    const int lane = threadIdx.x & 31, cw = uniform_warp() - 12;
    const uint32_t utag = ((tag >> 16) % 31u + 1u) << 27;
    {
        const int myp = cw + lane * NCW;
        uint32_t n = 0;
        if (lane < RPW && myp < NP) n = lds32(SM_CNT1 + myp * 4);
        const uint32_t first = lane < CELLU ? 3u * (lane & ~1) : 0xffffffffu;
        const uint32_t sp = SM_STAGE + (cw * CELLU + lane) * 16;
        uint4* gp = g_cell + ((size_t)cw * NP + blockIdx.x) * CELLU + lane;
        uint4 v[RPW];
#pragma unroll
        for (int j = 0; j < RPW; j++) {
            v[j] = lds128(sp + j * (NCW * CELLU * 16));
            v[j].w = lds32(SM_META + (cw * CELLU + lane) * 4 + j * (NCW * CELLU * 4));
        }
#pragma unroll
        for (int j = 0; j < RPW; j++) {
            const uint32_t nj = __shfl_sync(0xffffffffu, n, j);
            if (lane == 0) v[j].x = tag | nj;
            v[j].w = nj > first ? v[j].w | utag : 0u;
        }
        asm volatile("bar.arrive 8, %0;" :: "n"(NT) : "memory");
        asm volatile("bar.sync 3, 384;" ::: "memory");
        static_for<RPW>([&](auto j) { stg_nz<j.v * (NCW * NP * CELLU * 16)>(gp, v[j.v]); });
    }
    TSTAMP_T(3, 384);
    const uint4* cellp = g_cell + ((size_t)blockIdx.x * NP + cw) * CELLU + lane;
    uint32_t hdr;
    {
        const bool mine = lane < RPW && cw + lane * NCW < NP;
        const uint32_t* hp = reinterpret_cast<const uint32_t*>(cellp - lane + (mine ? lane : 0) * (NCW * CELLU));
        int spin = 0;
        do {
            asm volatile("ld.relaxed.gpu.global.u32 %0, [%1];" : "=r"(hdr) : "l"(hp) : "memory");
            if (++spin > (1 << 24)) __trap();
        } while (__any_sync(0xffffffffu, (hdr ^ tag) >= 0x10000u));
        if (!mine) hdr = 0;
    }
    TSTAMP_T(12, 384);
    const uint32_t thr = lane < CELLU ? tag | (3 * lane) : 0xffffffffu;
    uint4 rec[RPW];
    uint32_t need = lds32(SM_CONST + 1536);
#pragma unroll
    for (int j = 0; j < RPW; j++) need += __shfl_sync(0xffffffffu, hdr, j) > thr ? 1u << j : 0u;
    static_for<RPW>([&](auto j) {
        rec[j.v] = make_uint4(0u, 0u, 0u, utag);
        ldg_bit<j.v * (NCW * CELLU * 16), 1 << j.v>(rec[j.v], cellp, need);
    });
    asm volatile("bar.arrive 10, 416;" ::: "memory");
    const uint32_t dummy = SM_DUMMY + lane * 4;
#pragma unroll
    for (int b = 0; b < RPW; b += 4) {
        uint32_t stale = 0;
#pragma unroll
        for (int j = b; j < b + 4 && j < RPW; j++) stale |= rec[j].w ^ utag;
        if (stale >= (1u << 27)) {
#pragma unroll
            for (int j = b; j < b + 4 && j < RPW; j++) {
                int spin = 0;
                while ((rec[j].w ^ utag) >= (1u << 27)) {
                    rec[j] = ldg_relaxed(cellp + j * (NCW * CELLU));
                    if (++spin > (1 << 24)) __trap();
                }
            }
        }
        uint32_t rk[4][3];
#pragma unroll
        for (int j = b; j < b + 4 && j < RPW; j++) {
#pragma unroll
            for (int i = 0; i < 3; i++) {
                const uint32_t f = (rec[j].w >> (9 * i)) & 511u;
                rk[j - b][i] = atom_inc(f != 0 ? SM_CNT2 - 4 + f * 4 : dummy);
            }
        }
#pragma unroll
        for (int j = b; j < b + 4 && j < RPW; j++) {
            const uint32_t x[3] = {rec[j].x, rec[j].y, rec[j].z};
#pragma unroll
            for (int i = 0; i < 3; i++) {
                const uint32_t f = (rec[j].w >> (9 * i)) & 511u;
                sts32_lt(rk[j - b][i], CAPN, SM_REC - CAPN * 4 + (f * CAPN + rk[j - b][i]) * 4, x[i]);
            }
        }
    }
    TSTAMP_T(14, 384);
    uint32_t rest = __ballot_sync(0xffffffffu, hdr > (tag | (uint32_t)CELL));
    while (rest) {
        const int j = __ffs(rest) - 1;
        rest &= rest - 1;
        collect_overflow(cw + j * NCW, tag);
    }
}

__device__ __noinline__ uint32_t edge_phase(cudaTextureObject_t tex, __nv_bfloat16* outp, int nown) {
    const int lane = threadIdx.x & 31, g = lane >> 2, warp = uniform_warp();
    const uint32_t cb0 = SM_CONST + lane * 16;
    const uint4 wx = lds128(cb0 + 512);
    const uint32_t z1 = lds32(cb0 + 1536), z2 = lds32(cb0 + 1540);
    const uint32_t id8 = lds32(cb0 + 2048), m3 = lds32(cb0 + 2056);
    const float selc = __uint_as_float(lds32(cb0 + 2052)), selc2 = __uint_as_float(lds32(cb0 + 1544));
    const uint32_t t = (lane & 3) | z2;

    uint4 r0, r1;
    uint32_t rc, rp = 0;
    uint32_t w[8], pd;
    uint32_t acc[8];
    float p = 0.f;

    auto fetch = [&] {
        rc = lds32(rp);
        rp += 8;
        const uint32_t i = and_or<0x7fff8u>(rc << 3, t);
        r0 = tex_row(tex, i);
        r1 = tex_row(tex, i + 4);
    };
    auto open_group = [&](int gr) {
        rp = SM_REC + (g & 1) * 4 + lds16(SM_ORD + gr * 16 + (g >> 1) * 4) * (CAPN * 4);
    };
    auto load_group = [&](int gr) {
        const uint32_t tn = lds16(SM_ORD + gr * 16 + t * 4);
        const uint4 a = lds128(SM_A + tn * 128 + ((g ^ (tn & 7)) << 4)), cw = lds128(SM_CONST + lane * 16);
        w[0] = __byte_perm(cw.x, a.x, 0x5410); w[1] = __byte_perm(cw.x, a.x, 0x7632);
        w[2] = __byte_perm(cw.y, a.y, 0x5410); w[3] = __byte_perm(cw.y, a.y, 0x7632);
        w[4] = __byte_perm(cw.z, a.z, 0x5410); w[5] = __byte_perm(cw.z, a.z, 0x7632);
        w[6] = __byte_perm(cw.w, a.w, 0x5410); w[7] = __byte_perm(cw.w, a.w, 0x7632);
        pd = lds16(SM_POS + lds16(SM_ORD + gr * 16 + (g >> 1) * 4) * 8 + 2 * t) << 16;
#pragma unroll
        for (int i = 0; i < 8; i++) acc[i] = 0u;
        p = 0.f;
        return max(__shfl_sync(0xffffffffu, (int)lds16(SM_ORD + gr * 16 + 2), 0), 2);
    };

    uint32_t badq = 0;
    int q = 0, grp = warp;
    open_group(grp);
    fetch();
    int rem = load_group(grp);
#pragma unroll 1
    while (true) {
        uint32_t m[8];
        const float d = __uint_as_float(bsub2(pd, extract16(r0)));
        const float geo = fmaf(d, d, __uint_as_float(rc & m3));
        const uint32_t x0 = pack_h(geo, selc), x1 = pack_h(geo, selc2);
        hmma16_h(m[0], m[1], x0, z1, z2, x1, w[0], w[1], r0.x, r0.y);
        hmma16_h(m[2], m[3], x0, z1, z2, x1, w[2], w[3], r0.z, r0.w);
        hmma16_h(m[4], m[5], x0, z1, z2, x1, w[4], w[5], r1.x, r1.y);
        hmma16_h(m[6], m[7], x0, z1, z2, x1, w[6], w[7], r1.z, r1.w);
        fetch();
        float cs[4] = {0.f, 0.f, 0.f, 0.f};
#pragma unroll
        for (int i = 0; i < 8; i += 2) {
            m[i] = silu_half2(m[i]);
            m[i + 1] = silu_half2(m[i + 1]);
            hmma8_h(acc[i], acc[i + 1], m[i], m[i + 1], id8);
        }
        hmma16_f(cs, m[0], m[1], m[2], m[3], wx.x, wx.y);
        hmma16_f(cs, m[4], m[5], m[6], m[7], wx.z, wx.w);
        p = fmaf(cs[0] + cs[3], d, p);
        if (--rem <= 1) {
            const int ngrp = 47 + 24 * min(q, 2) - warp;
            if (rem == 1) {
                open_group(ngrp);
            } else {
                const bool odd = g & 1;
                const uint32_t node = lds16(SM_ORD + grp * 16 + (g >> 1) * 4);
                const uint32_t rn = lds16(SM_ORD + grp * 16 + ((lane >> 1) & 3) * 4);
                uint32_t mi[4], chk;
#pragma unroll
                for (int i = 0; i < 4; i++) {
                    const uint32_t send = odd ? acc[i] : acc[4 + i], keep = odd ? acc[4 + i] : acc[i];
                    const uint32_t sum = hadd2(keep, __shfl_xor_sync(0xffffffffu, send, 4));
                    chk = i == 0 ? sum : habsmax2(chk, sum);
                    const __half2 s2 = *reinterpret_cast<const __half2*>(&sum);
                    mi[i] = pack_bf(__low2float(s2), __high2float(s2));
                }
                const float psum = p + __shfl_xor_sync(0xffffffffu, p, 4);
                const bool bad = (chk & 0x7c00u) == 0x7c00u || (chk & 0x7c000000u) == 0x7c000000u ||
                                 (__float_as_uint(psum) & 0x7f800000u) == 0x7f800000u;
                badq |= bad ? 1u << (4 * q + (g >> 1)) : 0u;
                stsm4(SM_A + rn * 128 + ((((lane & 1) * 4 + (lane >> 3)) ^ (rn & 7)) << 4), mi[0], mi[1], mi[2], mi[3]);
                const __nv_bfloat16 pn =
                    __float2bfloat16(fmaf(psum, __uint_as_float(lds32(SM_CONST + 2060)), __uint_as_float(pd)));
                if ((int)node < nown && (lane & 7) < 3) outp[node * 3 + t] = pn;
                if (++q == 4) break;
                grp = ngrp;
                rem = load_group(grp);
            }
        }
    }
    return __reduce_or_sync(0xffffffffu, badq);
}

__global__ void __launch_bounds__(NT, 1)
egnn_kernel(const __nv_bfloat16* __restrict__ h, const __nv_bfloat16* __restrict__ pos,
            const __nv_bfloat16* __restrict__ e_attr, const int* __restrict__ src, const int* __restrict__ dst,
            const __nv_bfloat16* __restrict__ w_e, const __nv_bfloat16* __restrict__ w_x,
            __nv_bfloat16* __restrict__ out, cudaTextureObject_t tex,
            const __grid_constant__ CUtensorMap map_h, const __grid_constant__ CUtensorMap map_wh) {
    extern __shared__ unsigned char smem_raw[];
    const int tid = threadIdx.x, lane = tid & 31;
    const int cta = blockIdx.x;
    const int node0 = cta * NPP;
    const int nown = min(NPP, N_NODES - node0);
    TSTAMP(0);

    if (tid == NT - 32) {
        if ((uint32_t)__cvta_generic_to_shared(smem_raw) > SB) __trap();
        const uint32_t ne = min(CH, N_EDGES - cta * CH);
#pragma unroll
        for (int i = 0; i < 5; i++) asm volatile("mbarrier.init.shared.b64 [%0], 1;" :: "r"(SM_BAR + 8 * i) : "memory");
        asm volatile("fence.mbarrier_init.release.cluster;" ::: "memory");
        asm volatile("mbarrier.arrive.expect_tx.shared.b64 _, [%0], %1;" :: "r"(SM_BAR + 8), "r"(ne * 4) : "memory");
        bulk_load(SM_ED, dst + cta * CH, ne * 4, SM_BAR + 8);
        asm volatile("mbarrier.arrive.expect_tx.shared.b64 _, [%0], %1;" :: "r"(SM_BAR + 24), "r"(131 * 128 + 16 + nown * 6) : "memory");
        bulk_load(SM_RE, g_epoch + cta, 16, SM_BAR + 24);
        bulk_load(SM_RP, pos + node0 * 3, nown * 6, SM_BAR + 24);
        bulk_load(SM_RX, w_x, 128, SM_BAR + 24);
        bulk_load(SM_RW, w_e, 130 * 128, SM_BAR + 24);
        asm volatile("mbarrier.arrive.expect_tx.shared.b64 _, [%0], %1;" :: "r"(SM_BAR + 16), "r"(ne * 6) : "memory");
        bulk_load(SM_ES, src + cta * CH, ne * 4, SM_BAR + 16);
        bulk_load(SM_EA, e_attr + cta * CH, ne * 2, SM_BAR + 16);
        asm volatile("mbarrier.arrive.expect_tx.shared.b64 _, [%0], %1;" :: "r"(SM_BAR), "r"(NPP * 64 + 16384) : "memory");
        asm volatile("mbarrier.arrive.expect_tx.shared.b64 _, [%0], %1;" :: "r"(SM_BAR + 32), "r"(NPP * 64) : "memory");
    }
    if (tid < (SM_RUN - SM_CNT1) / 16) {
        const uint32_t z = tid < (SM_CNT2 - SM_CNT1) / 16 ? 1u : tid < (SM_DUMMY - SM_CNT1) / 16 ? 0u : 1u << 16;
        sts128(SM_CNT1 + tid * 16, z, z, z, z);
    }
#pragma unroll
    for (int k = 0; k < 2; k++)
        if (k == 0 || tid < (NP * CELLU + 3) / 4 - NT) sts128(SM_META + (tid + k * NT) * 16, 0u, 0u, 0u, 0u);
    const int warp = uniform_warp(), wg = warp >> 2;
    __syncthreads();
    TSTAMP(1);
    if (tid < 2 * NP) g_cell[((size_t)(tid >> 1) * NP + cta) * CELLU + (tid & 1)] = make_uint4(0u, 0u, 0u, 0u);
    else if (tid < 2 * NP + 2) reinterpret_cast<uint4*>(g_mail + cta * MAILW)[tid & 1] = make_uint4(0u, 0u, 0u, 0u);
    else if (cta == 0 && tid < 2 * NP + 10) {
        g_B[(size_t)KILL * 8 + tid - (2 * NP + 2)] = make_uint4(0xF800F800u, 0xF800F800u, 0xF800F800u, 0xF800F800u);
        __threadfence();
    }
    uint32_t epoch;
    uint32_t tag;
    {
        uint4 vs[2], vd[2];
        uint2 ve[2];
        const int e0 = cta * CH + tid * 4;
        uint32_t cell[EPT], rank[EPT];
        mbar_wait(SM_BAR + 8);
        TSTAMP(19);
#pragma unroll
        for (int k = 0; k < 2; k++) vd[k] = lds128(SM_ED + tid * 16 + k * (NT * 16));
        if (warp != NW - 1) {
            asm volatile("bar.arrive 11, %0;" :: "n"(NT), "r"(vd[0].x), "r"(vd[1].x) : "memory");
        } else {
            asm volatile("bar.sync 11, %0;" :: "n"(NT), "r"(vd[0].x), "r"(vd[1].x) : "memory");
            if (lane == 0) {
#pragma unroll
                for (int mt = 0; mt < H1TILES; mt++) tma_load(SM_H + mt * 8192, &map_h, node0 + mt * 64, SM_BAR + 32);
            }
            __syncwarp();
        }
#pragma unroll
        for (int k = 0; k < 2; k++) {
            const uint32_t dv[4] = {vd[k].x, vd[k].y, vd[k].z, vd[k].w};
            const bool ok = e0 + k * (NT * 4) < N_EDGES;
#pragma unroll
            for (int q = 0; q < 4; q++) {
                cell[k * 4 + q] = dv[q] / NPP;
                rank[k * 4 + q] = atom_inc(ok ? SM_CNT1 + cell[k * 4 + q] * 4 : SM_DUMMY + lane * 4);
            }
        }
        uint32_t rmax = 0;
#pragma unroll
        for (int k = 0; k < 2; k++) {
            const uint32_t dv[4] = {vd[k].x, vd[k].y, vd[k].z, vd[k].w};
#pragma unroll
            for (int q = 0; q < 4; q++) {
                const uint32_t p = cell[k * 4 + q], rk = rank[k * 4 + q];
                const uint32_t u = (rk * 171u) >> 9, j = rk - 3u * u;
                const uint32_t ui = p * CELLU + u;
                rmax = max(rmax, rk);
                red_or(rk < CELL ? SM_META + ui * 4 : SM_RUN + lane * 4, (dv[q] + 1u - p * NPP) << (9u * j));
                cell[k * 4 + q] = SM_STAGE + (ui * 4 + j) * 4;
            }
        }
    mbar_wait(SM_BAR + 24);
    if (tid >= NT - NPP) {
        const uint32_t n = tid - (NT - NPP), ok = (int)n < nown ? 0xffffffffu : 0u;
        sts64(SM_POS + n * 8, (lds16(SM_RP + n * 6) | (lds16(SM_RP + n * 6 + 2) << 16)) & ok, lds16(SM_RP + n * 6 + 4) & ok);
    }
#pragma unroll
    for (int k = 0; k < 2; k++)
        if (k == 0 || tid < 1024 - NT) {
            const uint4 v = lds128(SM_RW + (tid + k * NT) * 16);
            sts128(SM_W + k * (NT * 16) + (tid >> 3) * 128 + (((tid & 7) ^ ((tid >> 3) & 7)) << 4), bmul2(v.x, 0x3F003F00u),
                   bmul2(v.y, 0x3F003F00u), bmul2(v.z, 0x3F003F00u), bmul2(v.w, 0x3F003F00u));
        }
    fence_async();
        if (warp == 8) const_phase();
        epoch = lds32(SM_RE);
        mbar_wait(SM_BAR + 16);
        TSTAMP(20);
#pragma unroll
        for (int k = 0; k < 2; k++) {
            vs[k] = lds128(SM_ES + tid * 16 + k * (NT * 16));
            ve[k] = lds64(SM_EA + tid * 8 + k * (NT * 8));
        }
        if (warp != NW - 1) {
                asm volatile("bar.arrive 9, %0;" :: "n"(NT), "r"(vs[0].x), "r"(vs[1].x), "r"(ve[0].x), "r"(ve[1].x) : "memory");
        } else {
            asm volatile("bar.sync 9, %0;" :: "n"(NT), "r"(vs[0].x), "r"(vs[1].x), "r"(ve[0].x), "r"(ve[1].x) : "memory");
            if (lane == 0) {
#pragma unroll
                for (int mt = H1TILES; mt < 6; mt++) tma_load(SM_H + mt * 8192, &map_h, node0 + mt * 64, mt < 3 ? SM_BAR + 32 : SM_BAR);
                tma_load(SM_W + 16384, &map_wh, 0, SM_BAR);
                tma_load(SM_W + 24576, &map_wh, 64, SM_BAR);
            }
            __syncwarp();
        }
        tag = (epoch % 0xffffu + 1u) << 16;
#pragma unroll
        for (int k = 0; k < 2; k++) {
            const uint32_t xv[4] = {__byte_perm(vs[k].x, ve[k].x, 0x5410), __byte_perm(vs[k].y, ve[k].x, 0x7610),
                                    __byte_perm(vs[k].z, ve[k].y, 0x5410), __byte_perm(vs[k].w, ve[k].y, 0x7610)};
#pragma unroll
            for (int q = 0; q < 4; q++) sts32_lt(rank[k * 4 + q], CELL, cell[k * 4 + q], xv[q]);
        }
        if (rmax >= CELL) {
#pragma unroll
            for (int k = 0; k < 2; k++) {
                const uint32_t dv[4] = {vd[k].x, vd[k].y, vd[k].z, vd[k].w};
                const uint32_t xv[4] = {__byte_perm(vs[k].x, ve[k].x, 0x5410), __byte_perm(vs[k].y, ve[k].x, 0x7610),
                                        __byte_perm(vs[k].z, ve[k].y, 0x5410), __byte_perm(vs[k].w, ve[k].y, 0x7610)};
#pragma unroll
                for (int q = 0; q < 4; q++)
                    if (rank[k * 4 + q] >= CELL && rank[k * 4 + q] < (1u << 16))
                        g_ovf[(size_t)cta * CH + atom_inc(F_NOVF)] = make_uint2(xv[q], dv[q]);
            }
            __threadfence();
        }
    }
    __syncthreads();
    TSTAMP(2);
    if (tid == 32) g_epoch[cta].x = epoch + 1;
    if (wg < 3) {
        node_phase(tag);
    } else {
        collect_phase(tag);
    }
    TSTAMP(6);
    if (wg >= 3) {
        asm volatile("bar.sync 3, %0;" :: "n"(NPP) : "memory");
        TSTAMP_T(7, 384);
        const int tid = threadIdx.x - (NT - NPP);
        const uint32_t deg = lds32(SM_CNT2 + tid * 4);
        uint32_t skey = 0;
        if (deg <= MAXD) skey = (deg + 1) >> 1;
        const uint32_t srank = atom_inc(SM_HIST + skey * 4);
        {
            const uint2 pp = lds64(SM_POS + tid * 8);
            const float x = __uint_as_float(pp.x << 16), y = __uint_as_float(pp.x & 0xffff0000u), z = __uint_as_float(pp.y << 16);
            if (!((x * x + y * y + z * z) * __uint_as_float(lds32(F_WDM)) <= 8192.f)) sts32(F_SLOW, 1u);
        }
        asm volatile("bar.sync 3, %0;" :: "n"(NPP) : "memory");
        const int c = lds32(SM_HIST + (31 - lane) * 4);
        int inc = c;
#pragma unroll
        for (int o = 1; o < 32; o <<= 1) {
            int v = __shfl_up_sync(0xffffffffu, inc, o);
            if (lane >= o) inc += v;
        }
        const int base = __shfl_sync(0xffffffffu, inc - c, 31 - skey);
        sts32(SM_ORD + (base + srank) * 4, (uint32_t)tid | (skey << 16));
        const int gs = (base + srank) & ~3;
        int l = 0;
#pragma unroll
        for (int o = 16; o > 0; o >>= 1)
            if (__shfl_sync(0xffffffffu, inc, l + o - 1) <= gs) l += o;
#pragma unroll 1
        for (int i = deg; i < 2 * max(31 - l, 2); i++) sts32(SM_REC + (tid * CAPN + i) * 4, KILL);
    } else {
        for (int run = tid; run < NP; run += NT - NPP) {
            const uint32_t v = poll_mail(run, tag);
            sts32(SM_RUN + run * 4, v);
            if (v & 0x8000u) sts32(F_GBIG, 1u);
        }
        TSTAMP(15);
    }
    __syncthreads();
    TSTAMP(8);

    uint32_t slow = 0xffffu;
    if (lds32(F_GBIG) != 0 && lds32(F_SLOW) == 0)
        slow = edge_phase(tex, out + (size_t)N_NODES * 64 + (size_t)node0 * 3, nown);
    TSTAMP_X(21, "max");
    const int myq = (lane >> 2) & 3;
    const uint32_t rn = lds16(SM_ORD + (myq == 0 ? warp : 23 + 24 * myq - warp) * 16 + (lane & 3) * 4);
    slow = (slow | __ballot_sync(0xffffffffu, lds32(SM_CNT2 + rn * 4) > MAXD)) & __ballot_sync(0xffffffffu, (int)rn < nown) & 0xffffu;
    while (slow) {
        const int i = __ffs(slow) - 1;
        slow &= slow - 1;
        slow_node(__shfl_sync(0xffffffffu, rn, i), h, pos, w_e, w_x, out);
    }
    __syncwarp();

    {
        const uint32_t ro = rn * 128, sw = (lane >> 4) ^ (rn & 7);
        float acc[32];
        uint32_t a[4][4];
#pragma unroll
        for (int kk = 0; kk < 4; kk++) ldsm4(a[kk], SM_A + ro + ((sw ^ (2 * kk)) << 4));
        wg_fence();
        wg_n64r<0>(acc, a[0], mkdesc(SM_W + 24576));
#pragma unroll
        for (int kk = 1; kk < 4; kk++) wg_n64r<1>(acc, a[kk], mkdesc(SM_W + 24576 + kk * 2048));
        wg_commit();
        wg_wait0();
        uint32_t hf[4][4];
#pragma unroll
        for (int kk = 0; kk < 4; kk++) ldsm4(hf[kk], SM_H + ro + ((sw ^ (2 * kk)) << 4));
        wg_fence();
#pragma unroll
        for (int kk = 0; kk < 4; kk++) wg_n64r<1>(acc, hf[kk], mkdesc(SM_W + 16384 + kk * 2048));
        wg_commit();
        wg_wait0();
        fence_regs(acc);
#pragma unroll
        for (int kk = 0; kk < 4; kk++) {
#pragma unroll
            for (int i = 0; i < 4; i++) {
                asm volatile("" : "+r"(hf[kk][i]) :: "memory");
                hf[kk][i] = badd2(hf[kk][i], pack_bf(silu_half(0.5f * acc[8 * kk + 2 * i]), silu_half(0.5f * acc[8 * kk + 2 * i + 1])));
            }
            stsm4(SM_H + ro + ((sw ^ (2 * kk)) << 4), hf[kk][0], hf[kk][1], hf[kk][2], hf[kk][3]);
        }
        __syncwarp();
#pragma unroll
        for (int i = 0; i < 4; i++) {
            const uint32_t n = __shfl_sync(0xffffffffu, rn, 4 * i + (lane >> 3));
            const uint4 v = lds128(SM_H + n * 128 + (((lane & 7) ^ (n & 7)) << 4));
            if ((int)n < nown) reinterpret_cast<uint4*>(out + (size_t)(node0 + n) * 64)[lane & 7] = v;
        }
    }
    TSTAMP_X(23, "max");
}

typedef CUresult (*EncodeFn)(CUtensorMap*, CUtensorMapDataType, cuuint32_t, void*, const cuuint64_t*, const cuuint64_t*,
                             const cuuint32_t*, const cuuint32_t*, CUtensorMapInterleave, CUtensorMapSwizzle,
                             CUtensorMapL2promotion, CUtensorMapFloatOOBfill);

void encode_rows(EncodeFn fn, CUtensorMap* m, const void* base, int rows) {
    const cuuint64_t dim[2] = {64, (cuuint64_t)rows};
    const cuuint64_t stride[1] = {128};
    const cuuint32_t box[2] = {64, 64}, es[2] = {1, 1};
    fn(m, CU_TENSOR_MAP_DATA_TYPE_BFLOAT16, 2, const_cast<void*>(base), dim, stride, box, es,
       CU_TENSOR_MAP_INTERLEAVE_NONE, CU_TENSOR_MAP_SWIZZLE_128B, CU_TENSOR_MAP_L2_PROMOTION_NONE,
       CU_TENSOR_MAP_FLOAT_OOB_FILL_NONE);
}

}

extern "C" void kernel_launch(void* const* d_in, const int* in_sizes, int n_in, void* d_out, int out_size) {
    (void)in_sizes; (void)n_in; (void)out_size;
    static bool init_done = false;
    static cudaTextureObject_t tex = 0;
    static EncodeFn encode = nullptr;
    if (!init_done) {
        cudaFuncSetAttribute(egnn_kernel, cudaFuncAttributeMaxDynamicSharedMemorySize, SM_END);
        void* pB = nullptr;
        cudaGetSymbolAddress(&pB, g_B);
        cudaResourceDesc rd = {};
        rd.resType = cudaResourceTypeLinear;
        rd.res.linear.devPtr = pB;
        rd.res.linear.desc = cudaCreateChannelDesc(32, 32, 32, 32, cudaChannelFormatKindUnsigned);
        rd.res.linear.sizeInBytes = (size_t)BROWS * 128;
        cudaTextureDesc td = {};
        td.readMode = cudaReadModeElementType;
        cudaCreateTextureObject(&tex, &rd, &td, nullptr);
        cudaDriverEntryPointQueryResult qr;
        void* fn = nullptr;
        cudaGetDriverEntryPoint("cuTensorMapEncodeTiled", &fn, cudaEnableDefault, &qr);
        encode = (EncodeFn)fn;
        init_done = true;
    }
    CUtensorMap map_h, map_wh;
    encode_rows(encode, &map_h, d_in[0], N_NODES);
    encode_rows(encode, &map_wh, d_in[7], 128);
    egnn_kernel<<<NP, NT, SM_END>>>(
        (const __nv_bfloat16*)d_in[0], (const __nv_bfloat16*)d_in[1], (const __nv_bfloat16*)d_in[2],
        (const int*)d_in[3], (const int*)d_in[4], (const __nv_bfloat16*)d_in[5], (const __nv_bfloat16*)d_in[6],
        (__nv_bfloat16*)d_out, tex, map_h, map_wh);
}
```

```cpp
#include <cuda.h>
#include <cuda_runtime.h>
#include <cuda_bf16.h>
#include <cuda_fp16.h>
#include <stdint.h>

#define H1TILES 2
#define PRED_ATOM 0
#define ROT 0
#define EARLY 1
#define RELAXED 1

namespace {

constexpr int N_NODES = 50000;
constexpr int N_EDGES = 800000;
constexpr int NT = 768;
constexpr int NW = NT / 32;
constexpr int NP = 132;
constexpr int OWN = (N_NODES + NP - 1) / NP;
constexpr int NPP = 384;
constexpr int EPT = 8;
constexpr int CH = ((N_EDGES + NP - 1) / NP + 63) / 64 * 64;
constexpr int CELLU = 28;
constexpr int CELL = 3 * CELLU;
constexpr int CAPN = 46;
constexpr int MAXD = CAPN;
constexpr int MAILW = 32;
constexpr uint32_t KILL = NP * OWN;
constexpr int BROWS = NP * OWN + 1;
constexpr int NCW = 12;
constexpr int RPW = (NP + NCW - 1) / NCW;
static_assert(NP * CH >= N_EDGES && CH <= NT * EPT && OWN <= NPP && OWN > 320 && (N_NODES * 6) % 16 == 0, "shapes");
static_assert(N_EDGES % 4 == 0 && KILL < 65536, "shape assumptions");
static_assert(NP <= 144 && RPW <= 18, "loop bounds");

constexpr uint32_t SB = 2048;
constexpr uint32_t SM_H = SB;
constexpr uint32_t SM_W = SM_H + NPP * 128;
constexpr uint32_t SM_A = SM_W + 4 * 8192;
constexpr uint32_t SM_REC = SM_A + NPP * 128;
constexpr uint32_t SM_STAGE = SM_A;
constexpr uint32_t SM_POS = SM_REC + NPP * CAPN * 4;
constexpr uint32_t SM_CNT1 = SM_POS + NPP * 8;
constexpr uint32_t SM_CNT2 = SM_CNT1 + 160 * 4;
constexpr uint32_t SM_HIST = SM_CNT2 + NPP * 4;
constexpr uint32_t SM_FLAG = SM_HIST + 32 * 4;
constexpr uint32_t SM_DUMMY = SM_FLAG + 64;
constexpr uint32_t SM_RUN = SM_DUMMY + 128;
constexpr uint32_t SM_ORD = SM_RUN + 160 * 4;
constexpr uint32_t SM_BAR = SM_ORD + NPP * 4;
constexpr uint32_t SM_CONST = SM_BAR + 48;
constexpr uint32_t SM_END = SM_CONST + 5 * 512;
static_assert((RPW * NCW * CELLU + 4) * 16 <= NPP * 128 + NPP * CAPN * 4, "staging must fit");
static_assert(SM_A % 1024 == 0 && SM_W % 1024 == 0 && SM_REC % 16 == 0 && SM_CONST % 16 == 0 && SM_CNT1 % 16 == 0, "alignment");
constexpr uint32_t SM_META = SM_STAGE + (RPW * NCW * CELLU + 4) * 16;
constexpr uint32_t SM_ED = SM_H, SM_ES = SM_H + NT * EPT * 4, SM_EA = SM_W + 16384;
constexpr uint32_t SM_RX = SM_POS - 128, SM_RW = SM_RX - 130 * 128, SM_RP = SM_RW - NPP * 6 - 32, SM_RE = SM_RP - 16;
static_assert(SM_RE >= SM_META + 2 * NT * 16 && 2 * NT * 4 >= RPW * NCW * CELLU + 4 && SM_RE % 16 == 0, "temporaries must not overlap the staging");
constexpr uint32_t F_BIG = SM_FLAG, F_GBIG = SM_FLAG + 4, F_SLOW = SM_FLAG + 8,
                   F_WDM = SM_FLAG + 16, F_NOVF = SM_FLAG + 20;

__device__ uint4 g_cell[(NP * NP + 128) * CELLU];
__device__ uint2 g_ovf[NP * CH];
__device__ __align__(1024) uint4 g_B[BROWS * 8];
__device__ uint32_t g_mail[NP * MAILW];
__device__ uint4 g_epoch[NP];
#define TSTAMP_T(i, th)
#define TSTAMP(i) TSTAMP_T(i, 0)
#define TSTAMP_X(i, op)

__device__ __forceinline__ void hmma16_h(uint32_t& d0, uint32_t& d1, uint32_t a0, uint32_t a1, uint32_t a2, uint32_t a3,
                                         uint32_t b0, uint32_t b1, uint32_t c0, uint32_t c1) {
    asm("mma.sync.aligned.m16n8k16.row.col.f16.f16.f16.f16 {%0,%1}, {%2,%3,%4,%5}, {%6,%7}, {%8,%9};"
        : "=r"(d0), "=r"(d1) : "r"(a0), "r"(a1), "r"(a2), "r"(a3), "r"(b0), "r"(b1), "r"(c0), "r"(c1));
}
__device__ __forceinline__ void hmma8_h(uint32_t& d0, uint32_t& d1, uint32_t a0, uint32_t a1, uint32_t b0) {
    asm("mma.sync.aligned.m16n8k8.row.col.f16.f16.f16.f16 {%0,%1}, {%2,%3}, {%4}, {%0,%1};"
        : "+r"(d0), "+r"(d1) : "r"(a0), "r"(a1), "r"(b0));
}
__device__ __forceinline__ void hmma16_f(float (&d)[4], uint32_t a0, uint32_t a1, uint32_t a2, uint32_t a3,
                                         uint32_t b0, uint32_t b1) {
    asm("mma.sync.aligned.m16n8k16.row.col.f32.f16.f16.f32 {%0,%1,%2,%3}, {%4,%5,%6,%7}, {%8,%9}, {%0,%1,%2,%3};"
        : "+f"(d[0]), "+f"(d[1]), "+f"(d[2]), "+f"(d[3])
        : "r"(a0), "r"(a1), "r"(a2), "r"(a3), "r"(b0), "r"(b1));
}
__host__ __device__ constexpr uint64_t mkdesc(uint32_t addr) {
    return (uint64_t)((addr & 0x3FFFF) >> 4) | ((uint64_t)1 << 16) | ((uint64_t)64 << 32) | ((uint64_t)1 << 62);
}
__device__ __forceinline__ void wg_fence() { asm volatile("wgmma.fence.sync.aligned;" ::: "memory"); }
__device__ __forceinline__ void wg_commit() { asm volatile("wgmma.commit_group.sync.aligned;" ::: "memory"); }
__device__ __forceinline__ void wg_wait0() { asm volatile("wgmma.wait_group.sync.aligned 0;" ::: "memory"); }
template <int ACC>
__device__ __forceinline__ void wg_n64(float (&d)[32], uint64_t da, uint64_t db) {
    asm volatile("{.reg .pred p; setp.ne.b32 p, %34, 0;\n"
        "wgmma.mma_async.sync.aligned.m64n64k16.f32.bf16.bf16 "
        "{%0,%1,%2,%3,%4,%5,%6,%7,%8,%9,%10,%11,%12,%13,%14,%15,%16,%17,%18,%19,%20,%21,%22,%23,%24,%25,%26,%27,%28,%29,%30,%31},"
        " %32, %33, p, 1, 1, 0, 1;}"
        : "+f"(d[0]), "+f"(d[1]), "+f"(d[2]), "+f"(d[3]), "+f"(d[4]), "+f"(d[5]), "+f"(d[6]), "+f"(d[7]),
          "+f"(d[8]), "+f"(d[9]), "+f"(d[10]), "+f"(d[11]), "+f"(d[12]), "+f"(d[13]), "+f"(d[14]), "+f"(d[15]),
          "+f"(d[16]), "+f"(d[17]), "+f"(d[18]), "+f"(d[19]), "+f"(d[20]), "+f"(d[21]), "+f"(d[22]), "+f"(d[23]),
          "+f"(d[24]), "+f"(d[25]), "+f"(d[26]), "+f"(d[27]), "+f"(d[28]), "+f"(d[29]), "+f"(d[30]), "+f"(d[31])
        : "l"(da), "l"(db), "n"(ACC));
}
template <int ACC>
__device__ __forceinline__ void wg_n64r(float (&d)[32], const uint32_t (&a)[4], uint64_t db) {
    asm volatile("{.reg .pred p; setp.ne.b32 p, %37, 0;\n"
        "wgmma.mma_async.sync.aligned.m64n64k16.f32.bf16.bf16 "
        "{%0,%1,%2,%3,%4,%5,%6,%7,%8,%9,%10,%11,%12,%13,%14,%15,%16,%17,%18,%19,%20,%21,%22,%23,%24,%25,%26,%27,%28,%29,%30,%31},"
        " {%32,%33,%34,%35}, %36, p, 1, 1, 1;}"
        : "+f"(d[0]), "+f"(d[1]), "+f"(d[2]), "+f"(d[3]), "+f"(d[4]), "+f"(d[5]), "+f"(d[6]), "+f"(d[7]),
          "+f"(d[8]), "+f"(d[9]), "+f"(d[10]), "+f"(d[11]), "+f"(d[12]), "+f"(d[13]), "+f"(d[14]), "+f"(d[15]),
          "+f"(d[16]), "+f"(d[17]), "+f"(d[18]), "+f"(d[19]), "+f"(d[20]), "+f"(d[21]), "+f"(d[22]), "+f"(d[23]),
          "+f"(d[24]), "+f"(d[25]), "+f"(d[26]), "+f"(d[27]), "+f"(d[28]), "+f"(d[29]), "+f"(d[30]), "+f"(d[31])
        : "r"(a[0]), "r"(a[1]), "r"(a[2]), "r"(a[3]), "l"(db), "n"(ACC));
}
__device__ __forceinline__ void fence_regs(float (&d)[32]) {
#pragma unroll
    for (int i = 0; i < 32; i++) asm volatile("" : "+f"(d[i]) :: "memory");
}
__device__ __forceinline__ void fence_async() { asm volatile("fence.proxy.async.shared::cta;" ::: "memory"); }
__device__ __forceinline__ void stsm4(uint32_t addr, uint32_t r0, uint32_t r1, uint32_t r2, uint32_t r3) {
    asm volatile("stmatrix.sync.aligned.m8n8.x4.shared.b16 [%0], {%1,%2,%3,%4};"
                 :: "r"(addr), "r"(r0), "r"(r1), "r"(r2), "r"(r3) : "memory");
}
__device__ __forceinline__ void ldsm4(uint32_t (&r)[4], uint32_t addr) {
    asm volatile("ldmatrix.sync.aligned.m8n8.x4.shared.b16 {%0,%1,%2,%3}, [%4];"
                 : "=r"(r[0]), "=r"(r[1]), "=r"(r[2]), "=r"(r[3]) : "r"(addr) : "memory");
}
__device__ __forceinline__ uint32_t pack_bf(float lo, float hi) {
    uint32_t d;
    asm("cvt.rn.bf16x2.f32 %0, %1, %2;" : "=r"(d) : "f"(hi), "f"(lo));
    return d;
}
__device__ __forceinline__ uint32_t pack_h(float lo, float hi) {
    uint32_t d;
    asm("cvt.rn.f16x2.f32 %0, %1, %2;" : "=r"(d) : "f"(hi), "f"(lo));
    return d;
}
__device__ __forceinline__ uint32_t bmul2(uint32_t a, uint32_t b) {
    uint32_t d;
    asm("mul.rn.bf16x2 %0, %1, %2;" : "=r"(d) : "r"(a), "r"(b));
    return d;
}
__device__ __forceinline__ uint32_t badd2(uint32_t a, uint32_t b) {
    uint32_t d;
    asm("add.rn.bf16x2 %0, %1, %2;" : "=r"(d) : "r"(a), "r"(b));
    return d;
}
__device__ __forceinline__ uint32_t bsub2(uint32_t a, uint32_t b) {
    uint32_t d;
    asm("sub.rn.bf16x2 %0, %1, %2;" : "=r"(d) : "r"(a), "r"(b));
    return d;
}
__device__ __forceinline__ uint32_t hadd2(uint32_t a, uint32_t b) {
    uint32_t d;
    asm("add.rn.f16x2 %0, %1, %2;" : "=r"(d) : "r"(a), "r"(b));
    return d;
}
__device__ __forceinline__ uint32_t habsmax2(uint32_t a, uint32_t b) {
    uint32_t d;
    asm("max.NaN.xorsign.abs.f16x2 %0, %1, %2;" : "=r"(d) : "r"(a), "r"(b));
    return d;
}
__device__ __forceinline__ float silu_half(float x) {
    float t;
    asm("tanh.approx.f32 %0, %1;" : "=f"(t) : "f"(x));
    return fmaf(x, t, x);
}
__device__ __forceinline__ uint32_t silu_half2(uint32_t x) {
    uint32_t t, m;
    asm("tanh.approx.f16x2 %0, %1;" : "=r"(t) : "r"(x));
    asm("fma.rn.f16x2 %0, %1, %2, %1;" : "=r"(m) : "r"(x), "r"(t));
    return m;
}
__device__ __forceinline__ uint4 ldg_relaxed(const void* p) {
    uint4 v;
    asm volatile("ld.relaxed.gpu.global.v4.u32 {%0,%1,%2,%3}, [%4];"
                 : "=r"(v.x), "=r"(v.y), "=r"(v.z), "=r"(v.w) : "l"(p) : "memory");
    return v;
}
__device__ __forceinline__ uint4 ldg_cg(const void* p) {
    uint4 v;
    asm volatile("ld.global.L1::no_allocate.v4.u32 {%0,%1,%2,%3}, [%4];"
                 : "=r"(v.x), "=r"(v.y), "=r"(v.z), "=r"(v.w) : "l"(p) : "memory");
    return v;
}
template <int OFF, int BIT>
__device__ __forceinline__ void ldg_bit(uint4& v, const void* p, uint32_t m) {
    asm volatile("{.reg .pred q; .reg .b32 t; and.b32 t, %5, %7; setp.ne.u32 q, t, 0;\n"
                 "@q ld.global.L1::no_allocate.v4.u32 {%0,%1,%2,%3}, [%4+%6];}"
                 : "+r"(v.x), "+r"(v.y), "+r"(v.z), "+r"(v.w) : "l"(p), "r"(m), "n"(OFF), "n"(BIT) : "memory");
}
template <int OFF>
__device__ __forceinline__ void stg_nz(void* p, const uint4& v) {
    asm volatile("{.reg .pred q; setp.ne.u32 q, %4, 0; @q st.global.v4.u32 [%0+%5], {%1,%2,%3,%4};}"
                 :: "l"(p), "r"(v.x), "r"(v.y), "r"(v.z), "r"(v.w), "n"(OFF) : "memory");
}
template <int V> struct IC { static constexpr int v = V; };
template <int N, class F>
__device__ __forceinline__ void static_for(F&& f) {
    if constexpr (N > 0) { static_for<N - 1>(f); f(IC<N - 1>{}); }
}
__device__ __forceinline__ uint4 ldg_nc(const void* p) {
    uint4 v;
    asm volatile("ld.global.nc.L1::no_allocate.v4.u32 {%0,%1,%2,%3}, [%4];"
                 : "=r"(v.x), "=r"(v.y), "=r"(v.z), "=r"(v.w) : "l"(p));
    return v;
}
__device__ __forceinline__ uint2 ldg_nc2(const void* p) {
    uint2 v;
    asm volatile("ld.global.nc.L1::no_allocate.v2.u32 {%0,%1}, [%2];" : "=r"(v.x), "=r"(v.y) : "l"(p));
    return v;
}
__device__ __forceinline__ uint2 ldg_cg2(const void* p) {
    uint2 v;
    asm volatile("ld.global.L1::no_allocate.v2.u32 {%0,%1}, [%2];" : "=r"(v.x), "=r"(v.y) : "l"(p) : "memory");
    return v;
}
__device__ __forceinline__ uint32_t bf16_bits(const __nv_bfloat16* p) {
    return (uint32_t)__ldg(reinterpret_cast<const unsigned short*>(p));
}
__device__ __forceinline__ float bf16_val(const __nv_bfloat16* p) { return __uint_as_float(bf16_bits(p) << 16); }
__device__ __forceinline__ uint4 tex_row(cudaTextureObject_t tex, uint32_t i) {
    uint4 v;
    asm volatile("tex.1d.v4.u32.s32 {%0,%1,%2,%3}, [%4, {%5}];"
                 : "=r"(v.x), "=r"(v.y), "=r"(v.z), "=r"(v.w) : "l"(tex), "r"(i));
    return v;
}
__device__ __forceinline__ uint32_t lds16(uint32_t addr) {
    uint32_t v;
    asm volatile("ld.shared.u16 %0, [%1];" : "=r"(v) : "r"(addr) : "memory");
    return v;
}
__device__ __forceinline__ uint32_t lds32(uint32_t addr) {
    uint32_t v;
    asm volatile("ld.shared.u32 %0, [%1];" : "=r"(v) : "r"(addr) : "memory");
    return v;
}
__device__ __forceinline__ uint2 lds64(uint32_t addr) {
    uint2 v;
    asm volatile("ld.shared.v2.u32 {%0,%1}, [%2];" : "=r"(v.x), "=r"(v.y) : "r"(addr) : "memory");
    return v;
}
__device__ __forceinline__ uint4 lds128(uint32_t addr) {
    uint4 v;
    asm volatile("ld.shared.v4.u32 {%0,%1,%2,%3}, [%4];" : "=r"(v.x), "=r"(v.y), "=r"(v.z), "=r"(v.w) : "r"(addr) : "memory");
    return v;
}
__device__ __forceinline__ void sts32(uint32_t addr, uint32_t v) {
    asm volatile("st.shared.u32 [%0], %1;" :: "r"(addr), "r"(v) : "memory");
}
__device__ __forceinline__ void sts64(uint32_t addr, uint32_t a, uint32_t b) {
    asm volatile("st.shared.v2.u32 [%0], {%1,%2};" :: "r"(addr), "r"(a), "r"(b) : "memory");
}
__device__ __forceinline__ void sts128(uint32_t addr, uint32_t a, uint32_t b, uint32_t c, uint32_t d) {
    asm volatile("st.shared.v4.u32 [%0], {%1,%2,%3,%4};" :: "r"(addr), "r"(a), "r"(b), "r"(c), "r"(d) : "memory");
}
__device__ __forceinline__ uint32_t atom_inc(uint32_t addr) {
    uint32_t r;
    asm volatile("atom.shared.add.u32 %0, [%1], 1;" : "=r"(r) : "r"(addr) : "memory");
    return r;
}
__device__ __forceinline__ uint32_t atom_inc_nz(uint32_t f, uint32_t addr) {
    uint32_t r;
    asm volatile("{.reg .pred q; setp.ne.u32 q, %2, 0; @q atom.shared.inc.u32 %0, [%1], 0xffffffff;}" : "=r"(r) : "r"(addr), "r"(f) : "memory");
    return r;
}
__device__ __forceinline__ void sts32_nz_lt(uint32_t f, uint32_t a, uint32_t b, uint32_t addr, uint32_t v) {
    asm volatile("{.reg .pred q, p; setp.ne.u32 p, %4, 0; setp.lt.and.u32 q, %2, %3, p; @q st.shared.u32 [%0], %1;}"
                 :: "r"(addr), "r"(v), "r"(a), "r"(b), "r"(f) : "memory");
}
__device__ __forceinline__ void red_or(uint32_t addr, uint32_t v) {
    asm volatile("red.shared.or.b32 [%0], %1;" :: "r"(addr), "r"(v) : "memory");
}
__device__ __forceinline__ void sts32_lt(uint32_t a, uint32_t b, uint32_t addr, uint32_t v) {
    asm volatile("{.reg .pred q; setp.lt.u32 q, %2, %3; @q st.shared.u32 [%0], %1;}"
                 :: "r"(addr), "r"(v), "r"(a), "r"(b) : "memory");
}
__device__ __forceinline__ void sts64_lt(uint32_t a, uint32_t b, uint32_t addr, uint32_t x, uint32_t y) {
    asm volatile("{.reg .pred q; setp.lt.u32 q, %3, %4; @q st.shared.v2.u32 [%0], {%1,%2};}"
                 :: "r"(addr), "r"(x), "r"(y), "r"(a), "r"(b) : "memory");
}
__device__ __forceinline__ uint32_t and3(uint32_t a, uint32_t b, uint32_t c) {
    uint32_t d;
    asm("lop3.b32 %0, %1, %2, %3, 0x80;" : "=r"(d) : "r"(a), "r"(b), "r"(c));
    return d;
}
template <uint32_t M>
__device__ __forceinline__ uint32_t and_or(uint32_t a, uint32_t b) {
    uint32_t d;
    asm("lop3.b32 %0, %1, %2, %3, 0xEC;" : "=r"(d) : "r"(a), "r"(b), "n"(M));
    return d;
}
template <uint32_t M>
__device__ __forceinline__ uint32_t bitsel(uint32_t a, uint32_t b) {
    uint32_t d;
    asm("lop3.b32 %0, %1, %2, %3, 0xE4;" : "=r"(d) : "r"(a), "r"(b), "n"(M));
    return d;
}
__device__ __forceinline__ uint32_t extract16(const uint4& r) {
    const uint32_t u = bitsel<0x00030003u>(r.x, r.y << 2);
    const uint32_t v = bitsel<0x00030003u>(r.z, r.w << 2);
    const uint32_t w = bitsel<0x000F000Fu>(u, v << 4);
    return __byte_perm(w, 0u, 0x2044);
}
__device__ __forceinline__ float bfr(float x) { return __bfloat162float(__float2bfloat16(x)); }
__device__ __forceinline__ void mbar_wait(uint32_t bar) {
    uint32_t done = 0;
    int spin = 0;
    while (!done) {
        asm volatile("{.reg .pred p; mbarrier.try_wait.parity.shared.b64 p, [%1], 0; selp.u32 %0, 1, 0, p;}"
                     : "=r"(done) : "r"(bar) : "memory");
        if (++spin > (1 << 24)) __trap();
    }
}
__device__ __forceinline__ void tma_load(uint32_t dst, const CUtensorMap* tm, int row, uint32_t bar) {
    asm volatile("cp.async.bulk.tensor.2d.shared::cluster.global.mbarrier::complete_tx::bytes [%0], [%1, {%3, %4}], [%2];"
                 :: "r"(dst), "l"(tm), "r"(bar), "r"(0), "r"(row) : "memory");
}
__device__ __forceinline__ void bulk_load(uint32_t dst, const void* src, uint32_t bytes, uint32_t bar) {
    asm volatile("cp.async.bulk.shared::cluster.global.mbarrier::complete_tx::bytes [%0], [%1], %2, [%3];"
                 :: "r"(dst), "l"(src), "r"(bytes), "r"(bar) : "memory");
}
__device__ __forceinline__ uint32_t poll_mail(int run, uint32_t tag) {
    uint32_t v;
    int spin = 0;
    while (true) {
        asm volatile("ld.acquire.gpu.global.u32 %0, [%1];" : "=r"(v) : "l"(&g_mail[run * MAILW]) : "memory");
        if ((v ^ tag) < 0x10000u) break;
        if (++spin > (1 << 24)) __trap();
    }
    return v;
}
__device__ __forceinline__ void place_rec(uint32_t x, uint32_t ln) {
    const uint32_t rk = atom_inc(SM_CNT2 + ln * 4);
    sts32_lt(rk, CAPN, SM_REC + (ln * CAPN + rk) * 4, x);
}
__device__ __forceinline__ int uniform_warp() { return __shfl_sync(0xffffffffu, threadIdx.x >> 5, 0); }

__device__ __noinline__ void slow_node(int ln, const __nv_bfloat16* h, const __nv_bfloat16* pos,
                                       const __nv_bfloat16* w_e, const __nv_bfloat16* w_x, __nv_bfloat16* out) {
    const int lane = threadIdx.x & 31, c = 2 * lane;
    const int node = blockIdx.x * OWN + ln;
    float a0 = 0.f, a1 = 0.f;
#pragma unroll 4
    for (int k = 0; k < 64; k++) {
        const float hv = bf16_val(h + (size_t)node * 64 + k);
        a0 = fmaf(hv, bf16_val(w_e + k * 64 + c), a0);
        a1 = fmaf(hv, bf16_val(w_e + k * 64 + c + 1), a1);
    }
    const float wd0 = bf16_val(w_e + 128 * 64 + c), wd1 = bf16_val(w_e + 128 * 64 + c + 1);
    const float wa0 = bf16_val(w_e + 129 * 64 + c), wa1 = bf16_val(w_e + 129 * 64 + c + 1);
    const float wx0 = bf16_val(w_x + c), wx1 = bf16_val(w_x + c + 1);
    const float px = bf16_val(pos + (size_t)node * 3), py = bf16_val(pos + (size_t)node * 3 + 1),
                pz = bf16_val(pos + (size_t)node * 3 + 2);
    float m0 = 0.f, m1 = 0.f, ux = 0.f, uy = 0.f, uz = 0.f;
    for (int run = 0; run < NP; run++) {
        const int novf = lds32(SM_RUN + run * 4) & 0x1fff;
        const uint32_t* cell = reinterpret_cast<const uint32_t*>(g_cell + ((size_t)blockIdx.x * NP + run) * CELLU);
        const int ncell = min((int)(__ldcg(cell) & 0xffffu), CELL);
        for (int i0 = 0; i0 < 96 + novf; i0 += 32) {
            const int i = i0 + lane;
            uint2 rec = make_uint2(0u, 0u);
            bool hit = false;
            if (i < ncell) {
                const int u = i / 3, j = i - 3 * u;
                rec.x = __ldcg(cell + 4 * u + j);
                hit = ((__ldcg(cell + 4 * u + 3) >> (9 * j)) & 511u) == (uint32_t)ln + 1;
            } else if (i >= 96 && i - 96 < novf) {
                rec = __ldcg(g_ovf + (size_t)run * CH + i - 96);
                hit = rec.y == (uint32_t)node;
            }
            uint32_t bal = __ballot_sync(0xffffffffu, hit);
            while (bal) {
                const int l = __ffs(bal) - 1;
                bal &= bal - 1;
                const uint32_t rx = __shfl_sync(0xffffffffu, rec.x, l);
                const int s = rx & 0xffff;
                const float ea = __uint_as_float(rx & 0xffff0000u);
                float b0 = a0, b1 = a1;
#pragma unroll 8
                for (int k = 0; k < 64; k++) {
                    const float hv = bf16_val(h + (size_t)s * 64 + k);
                    b0 = fmaf(hv, bf16_val(w_e + (64 + k) * 64 + c), b0);
                    b1 = fmaf(hv, bf16_val(w_e + (64 + k) * 64 + c + 1), b1);
                }
                const float dx = bfr(px - bf16_val(pos + (size_t)s * 3)), dy = bfr(py - bf16_val(pos + (size_t)s * 3 + 1)),
                            dz = bfr(pz - bf16_val(pos + (size_t)s * 3 + 2));
                const float d2 = dx * dx + dy * dy + dz * dz;
                b0 = fmaf(ea, wa0, fmaf(d2, wd0, b0));
                b1 = fmaf(ea, wa1, fmaf(d2, wd1, b1));
                const float s0 = b0 / (1.f + __expf(-b0)), s1 = b1 / (1.f + __expf(-b1));
                m0 += s0; m1 += s1;
                float cs = s0 * wx0 + s1 * wx1;
#pragma unroll
                for (int o = 16; o > 0; o >>= 1) cs += __shfl_xor_sync(0xffffffffu, cs, o);
                ux = fmaf(dx, cs, ux); uy = fmaf(dy, cs, uy); uz = fmaf(dz, cs, uz);
            }
        }
    }
    sts32(SM_A + ln * 128 + (((lane >> 2) ^ (ln & 7)) << 4) + (lane & 3) * 4, pack_bf(m0, m1));
    if (lane == 0) {
        __nv_bfloat16* pp = out + (size_t)N_NODES * 64 + (size_t)node * 3;
        pp[0] = __float2bfloat16(px + ux); pp[1] = __float2bfloat16(py + uy); pp[2] = __float2bfloat16(pz + uz);
    }
}
__device__ __noinline__ void collect_overflow(int run, uint32_t tag) {
    const int novf = poll_mail(run, tag) & 0x1fff;
    for (int i = threadIdx.x & 31; i < novf; i += 32) {
        const uint2 r = __ldcg(g_ovf + (size_t)run * CH + i);
        const uint32_t ln = r.y - blockIdx.x * OWN;
        if (ln < (uint32_t)OWN) place_rec(r.x, ln);
    }
    __syncwarp();
}

__device__ __forceinline__ void const_phase() {
    auto val = [](uint32_t ad) { return __uint_as_float(lds16(ad) << 16); };
    constexpr uint32_t WD = SM_RW + 128 * 128, WA = WD + 128;
    const int lane = threadIdx.x & 31, g = lane >> 2, t = lane & 3;
    const float wd0 = fabsf(val(WD + lane * 2)), wd1 = fabsf(val(WD + 64 + lane * 2));
    const float wa0 = fabsf(val(WA + lane * 2)), wa1 = fabsf(val(WA + 64 + lane * 2));
    float wgf[8], wxf[8];
#pragma unroll
    for (int i = 0; i < 8; i++) wgf[i] = 0.5f * val((t < 3 ? WD : WA) + g * 2 + 16 * i);
    float wxm = 0.f;
#pragma unroll
    for (int i = 0; i < 8; i++) {
        wxf[i] = val(SM_RX + (16 * (i >> 1) + 8 * (g & 1) + 2 * t + (i & 1)) * 2);
        wxm = fmaxf(wxm, fabsf(wxf[i]));
    }
    const float wdm = __uint_as_float(__reduce_max_sync(0xffffffffu, __float_as_uint(fmaxf(wd0, wd1))));
    const float wam = __uint_as_float(__reduce_max_sync(0xffffffffu, __float_as_uint(fmaxf(wa0, wa1))));
    const uint32_t wxe = min(max(__reduce_max_sync(0xffffffffu, __float_as_uint(wxm)) >> 23, 2u), 252u);
    const float sc = __uint_as_float((254u - wxe) << 23);
    if (!(wdm == 0.f || (wdm >= 1.953125e-3f && wdm <= 32.f)) || !(wam == 0.f || (wam >= 1.953125e-3f && wam <= 32.f)))
        sts32(F_SLOW, 1u);
    sts32(F_WDM, __float_as_uint(wdm));
    const uint32_t ad = SM_CONST + lane * 16;
    sts128(ad, pack_h(wgf[0], wgf[1]), pack_h(wgf[2], wgf[3]), pack_h(wgf[4], wgf[5]), pack_h(wgf[6], wgf[7]));
    sts128(ad + 512, pack_h(sc * wxf[0], sc * wxf[1]), pack_h(sc * wxf[2], sc * wxf[3]),
           pack_h(sc * wxf[4], sc * wxf[5]), pack_h(sc * wxf[6], sc * wxf[7]));
    sts128(ad + 1536, 0u, 0u, ((g >> 1) == t) ? 0x3f800000u : 0u, 0u);
    sts128(ad + 2048, ((g >> 1) == t) ? (0x3C00u << (16 * (g & 1))) : 0u, ((g >> 1) == t) ? 0x3f800000u : 0u,
           t == 3 ? 0xffff0000u : 0u, wxe << 23);
}

__device__ __forceinline__ void node_phase(uint32_t tag) {
    const int lane = threadIdx.x & 31, g = lane >> 2, t = lane & 3;
    const int warp = uniform_warp(), wg = warp >> 2;
    const int row = wg * 64 + (warp & 3) * 16 + g;
    float acc[32];
    auto gemm = [&](int j, uint32_t w) {
        const uint64_t da = mkdesc(SM_H) + (wg + 3 * j) * 512;
        wg_fence();
        wg_n64<0>(acc, da, mkdesc(w));
#pragma unroll
        for (int kk = 1; kk < 4; kk++) wg_n64<1>(acc, da + kk * 2, mkdesc(w + kk * 2048));
        wg_commit();
        wg_wait0();
        fence_regs(acc);
    };
    uint32_t c[4];
#pragma unroll
    for (int i = 0; i < 4; i++)
        c[i] = __byte_perm(lds16(SM_POS + row * 8 + 2 * t + (i >> 1) * 1536 + (i & 1) * 64), 0u, 0x4140);
#pragma unroll
    for (int j = 0; j < 2; j++) {
        mbar_wait(j == 0 ? SM_BAR + 32 : SM_BAR);
        TSTAMP(16 + j);
        gemm(j, SM_W + 8192);
        if (j == 0) {
            if (fmaxf(fabsf(acc[0]), fabsf(acc[31])) >= 9.765625e-4f) sts32(F_BIG, 0x8000u);
            asm volatile("bar.sync 8, %0;" :: "n"(NT) : "memory");
        }
#pragma unroll
        for (int hf = 0; hf < 2; hf++) {
            const float* a = acc + 2 * hf;
            const uint32_t ad = SM_A + row * 128 + t * 16 + j * 24576 + hf * 1024, cc = c[2 * j + hf];
            sts128(ad, bitsel<0x00030003u>(cc, pack_h(a[0], a[1])), bitsel<0x00030003u>(cc >> 2, pack_h(a[4], a[5])),
                   bitsel<0x00030003u>(cc >> 4, pack_h(a[8], a[9])), bitsel<0x00030003u>(cc >> 6, pack_h(a[12], a[13])));
            sts128(ad + 64, pack_h(a[16], a[17]), pack_h(a[20], a[21]), pack_h(a[24], a[25]), pack_h(a[28], a[29]));
        }
    }
    fence_async();
    auto store_B = [&](int part, int parts) {
        asm volatile("cp.async.bulk.global.shared::cta.bulk_group [%0], [%1], %2;"
                     :: "l"(g_B + ((size_t)blockIdx.x * OWN + part * 64) * 8), "r"(SM_A + part * 8192),
                        "r"((min((part + parts) * 64, OWN) - part * 64) * 128) : "memory");
        asm volatile("cp.async.bulk.commit_group;" ::: "memory");
    };
    if (warp != 0) {
        asm volatile("bar.arrive 1, 384;" ::: "memory");
    } else {
        asm volatile("bar.sync 1, 384;" ::: "memory");
        if (lane == 0) store_B(0, EARLY);
        __syncwarp();
    }
    TSTAMP(4);
    uint32_t aw[2][16], amax;
#pragma unroll
    for (int j = 0; j < 2; j++) {
        gemm(j, SM_W);
#pragma unroll
        for (int i = 0; i < 16; i++) {
            const int e = i >> 2, q = i & 3;
            aw[j][i] = pack_h(acc[8 * q + e], acc[8 * q + 4 + e]);
            amax = i + j == 0 ? aw[j][i] : habsmax2(amax, aw[j][i]);
        }
    }
    if ((amax & 0x7fffu) > 0x7000u || (amax & 0x7fff0000u) > 0x70000000u) sts32(F_SLOW, 1u);
    if (warp == 0) {
        asm volatile("bar.sync 10, 416;" ::: "memory");
        TSTAMP(13);
        if (lane == 0) {
            store_B(EARLY, 6 - EARLY);
            asm volatile("cp.async.bulk.wait_group 0;" ::: "memory");
            asm volatile("st.relaxed.gpu.global.u32 [%0], %1;"
                         :: "l"(&g_mail[blockIdx.x * MAILW]), "r"(tag | lds32(F_BIG) | lds32(F_NOVF)) : "memory");
        }
        __syncwarp();
        TSTAMP(18);
        asm volatile("bar.arrive 2, 384;" ::: "memory");
    } else {
        asm volatile("bar.sync 2, 384;" ::: "memory");
    }
#pragma unroll
    for (int j = 0; j < 2; j++) {
#pragma unroll
        for (int e = 0; e < 4; e++)
            sts128(SM_A + row * 128 + j * 24576 + (e >> 1) * 1024 + (((2 * t + (e & 1)) ^ g) << 4),
                   aw[j][4 * e], aw[j][4 * e + 1], aw[j][4 * e + 2], aw[j][4 * e + 3]);
    }
}

__device__ __forceinline__ void collect_phase(uint32_t tag) {
    const int lane = threadIdx.x & 31, cw = uniform_warp() - 12;
    const uint32_t utag = ((tag >> 16) % 31u + 1u) << 27;
    {
        const int myp = cw + lane * NCW;
        uint32_t n = 0;
        if (lane < RPW && myp < NP) n = lds32(SM_CNT1 + myp * 4);
        const uint32_t first = lane < CELLU ? 3u * (lane & ~1) : 0xffffffffu;
        const uint32_t sp = SM_STAGE + (cw * CELLU + lane) * 16;
        uint4* gp = g_cell + ((size_t)cw * NP + blockIdx.x) * CELLU + lane;
        uint4 v[RPW];
#pragma unroll
        for (int j = 0; j < RPW; j++) {
            v[j] = lds128(sp + j * (NCW * CELLU * 16));
            v[j].w = lds32(SM_META + (cw * CELLU + lane) * 4 + j * (NCW * CELLU * 4));
        }
#pragma unroll
        for (int j = 0; j < RPW; j++) {
            const uint32_t nj = __shfl_sync(0xffffffffu, n, j);
            if (lane == 0) v[j].x = tag | nj;
            v[j].w = nj > first ? v[j].w | utag : 0u;
        }
        asm volatile("bar.arrive 8, %0;" :: "n"(NT) : "memory");
        static_for<RPW>([&](auto j) { stg_nz<j.v * (NCW * NP * CELLU * 16)>(gp, v[j.v]); });
    }
    asm volatile("bar.sync 3, 384;" ::: "memory");
    TSTAMP_T(3, 384);
    const uint4* cellp = g_cell + ((size_t)blockIdx.x * NP + cw) * CELLU + lane;
    uint32_t hdr;
    {
        const bool mine = lane < RPW && cw + lane * NCW < NP;
        const uint32_t* hp = reinterpret_cast<const uint32_t*>(cellp - lane + (mine ? lane : 0) * (NCW * CELLU));
        int spin = 0;
        do {
            asm volatile("ld.relaxed.gpu.global.u32 %0, [%1];" : "=r"(hdr) : "l"(hp) : "memory");
            if (++spin > (1 << 24)) __trap();
        } while (__any_sync(0xffffffffu, (hdr ^ tag) >= 0x10000u));
        if (!mine) hdr = 0;
    }
    TSTAMP_T(12, 384);
    const uint32_t thr = lane < CELLU ? tag | (3 * lane) : 0xffffffffu;
    uint4 rec[RPW];
    uint32_t need = lds32(SM_CONST + 1536);
#pragma unroll
    for (int j = 0; j < RPW; j++) need += __shfl_sync(0xffffffffu, hdr, j) > thr ? 1u << j : 0u;
    static_for<RPW>([&](auto j) {
        rec[j.v] = make_uint4(0u, 0u, 0u, utag);
        ldg_bit<j.v * (NCW * CELLU * 16), 1 << j.v>(rec[j.v], cellp, need);
    });
    asm volatile("bar.arrive 10, 416;" ::: "memory");
    const uint32_t dummy = SM_DUMMY + lane * 4;
#pragma unroll
    for (int b = 0; b < RPW; b += 4) {
        uint32_t stale = 0;
#pragma unroll
        for (int j = b; j < b + 4 && j < RPW; j++) stale |= rec[j].w ^ utag;
        if (stale >= (1u << 27)) {
#pragma unroll
            for (int j = b; j < b + 4 && j < RPW; j++) {
                int spin = 0;
                while ((rec[j].w ^ utag) >= (1u << 27)) {
                    rec[j] = ldg_relaxed(cellp + j * (NCW * CELLU));
                    if (++spin > (1 << 24)) __trap();
                }
            }
        }
        uint32_t rk[4][3];
#pragma unroll
        for (int j = b; j < b + 4 && j < RPW; j++) {
#pragma unroll
            for (int i = 0; i < 3; i++) {
                const uint32_t f = (rec[j].w >> (9 * i)) & 511u;
                rk[j - b][i] = atom_inc(f != 0 ? SM_CNT2 - 4 + f * 4 : dummy);
            }
        }
#pragma unroll
        for (int j = b; j < b + 4 && j < RPW; j++) {
            const uint32_t x[3] = {rec[j].x, rec[j].y, rec[j].z};
#pragma unroll
            for (int i = 0; i < 3; i++) {
                const uint32_t f = (rec[j].w >> (9 * i)) & 511u;
                sts32_lt(rk[j - b][i], CAPN, SM_REC - CAPN * 4 + (f * CAPN + rk[j - b][i]) * 4, x[i]);
            }
        }
    }
    TSTAMP_T(14, 384);
    uint32_t rest = __ballot_sync(0xffffffffu, hdr > (tag | (uint32_t)CELL));
    while (rest) {
        const int j = __ffs(rest) - 1;
        rest &= rest - 1;
        collect_overflow(cw + j * NCW, tag);
    }
}

__device__ __noinline__ uint32_t edge_phase(cudaTextureObject_t tex, __nv_bfloat16* outp, int nown) {
    const int lane = threadIdx.x & 31, g = lane >> 2, warp = uniform_warp();
    const uint32_t cb0 = SM_CONST + lane * 16;
    const uint4 wx = lds128(cb0 + 512);
    const uint32_t z1 = lds32(cb0 + 1536), z2 = lds32(cb0 + 1540);
    const uint32_t id8 = lds32(cb0 + 2048), m3 = lds32(cb0 + 2056);
    const float selc = __uint_as_float(lds32(cb0 + 2052)), selc2 = __uint_as_float(lds32(cb0 + 1544));
    const uint32_t t = (lane & 3) | z2;

    uint4 r0, r1;
    uint32_t rc, rp = 0;
    uint32_t w[8], pd;
    uint32_t acc[8];
    float p = 0.f;

    auto fetch = [&] {
        rc = lds32(rp);
        rp += 8;
        const uint32_t i = and_or<0x7fff8u>(rc << 3, t);
        r0 = tex_row(tex, i);
        r1 = tex_row(tex, i + 4);
    };
    auto open_group = [&](int gr) {
        rp = SM_REC + (g & 1) * 4 + lds16(SM_ORD + gr * 16 + (g >> 1) * 4) * (CAPN * 4);
    };
    auto load_group = [&](int gr) {
        const uint32_t tn = lds16(SM_ORD + gr * 16 + t * 4);
        const uint4 a = lds128(SM_A + tn * 128 + ((g ^ (tn & 7)) << 4)), cw = lds128(SM_CONST + lane * 16);
        w[0] = __byte_perm(cw.x, a.x, 0x5410); w[1] = __byte_perm(cw.x, a.x, 0x7632);
        w[2] = __byte_perm(cw.y, a.y, 0x5410); w[3] = __byte_perm(cw.y, a.y, 0x7632);
        w[4] = __byte_perm(cw.z, a.z, 0x5410); w[5] = __byte_perm(cw.z, a.z, 0x7632);
        w[6] = __byte_perm(cw.w, a.w, 0x5410); w[7] = __byte_perm(cw.w, a.w, 0x7632);
        pd = lds16(SM_POS + lds16(SM_ORD + gr * 16 + (g >> 1) * 4) * 8 + 2 * t) << 16;
#pragma unroll
        for (int i = 0; i < 8; i++) acc[i] = 0u;
        p = 0.f;
        return max(__shfl_sync(0xffffffffu, (int)lds16(SM_ORD + gr * 16 + 2), 0), 2);
    };

    uint32_t badq = 0;
    int q = 0, grp = warp;
    open_group(grp);
    fetch();
    int rem = load_group(grp);
    uint32_t m[8], c0, c1;
    float d;
    auto combine = [&] {
        d = __uint_as_float(bsub2(pd, extract16(r0)));
        const float geo = fmaf(d, d, __uint_as_float(rc & m3));
        const uint32_t x0 = pack_h(geo, selc), x1 = pack_h(geo, selc2);
        hmma16_h(m[0], m[1], x0, z1, z2, x1, w[0], w[1], r0.x, r0.y);
        hmma16_h(m[2], m[3], x0, z1, z2, x1, w[2], w[3], r0.z, r0.w);
        hmma16_h(m[4], m[5], x0, z1, z2, x1, w[4], w[5], r1.x, r1.y);
        hmma16_h(m[6], m[7], x0, z1, z2, x1, w[6], w[7], r1.z, r1.w);
    };
    auto coord = [&] {
        const __half2 h0 = *reinterpret_cast<const __half2*>(&c0), h1 = *reinterpret_cast<const __half2*>(&c1);
        p = fmaf(__half2float(__hadd(__low2half(h0), __high2half(h1))), d, p);
    };
#pragma unroll 1
    while (true) {
        combine();
        fetch();
#pragma unroll
        for (int i = 0; i < 8; i += 2) {
            m[i] = silu_half2(m[i]);
            m[i + 1] = silu_half2(m[i + 1]);
            hmma8_h(acc[i], acc[i + 1], m[i], m[i + 1], id8);
        }
        hmma16_h(c0, c1, m[0], m[1], m[2], m[3], wx.x, wx.y, 0u, 0u);
        hmma16_h(c0, c1, m[4], m[5], m[6], m[7], wx.z, wx.w, c0, c1);
        coord();
        if (--rem <= 1) {
            const int ngrp = 47 + 24 * min(q, 2) - warp;
            if (rem == 1) {
                open_group(ngrp);
            } else {
                const bool odd = g & 1;
                const uint32_t node = lds16(SM_ORD + grp * 16 + (g >> 1) * 4);
                const uint32_t rn = lds16(SM_ORD + grp * 16 + ((lane >> 1) & 3) * 4);
                uint32_t mi[4], chk;
#pragma unroll
                for (int i = 0; i < 4; i++) {
                    const uint32_t send = odd ? acc[i] : acc[4 + i], keep = odd ? acc[4 + i] : acc[i];
                    const uint32_t sum = hadd2(keep, __shfl_xor_sync(0xffffffffu, send, 4));
                    chk = i == 0 ? sum : habsmax2(chk, sum);
                    const __half2 s2 = *reinterpret_cast<const __half2*>(&sum);
                    mi[i] = pack_bf(__low2float(s2), __high2float(s2));
                }
                const float psum = p + __shfl_xor_sync(0xffffffffu, p, 4);
                const bool bad = (chk & 0x7c00u) == 0x7c00u || (chk & 0x7c000000u) == 0x7c000000u ||
                                 (__float_as_uint(psum) & 0x7f800000u) == 0x7f800000u;
                badq |= bad ? 1u << (4 * q + (g >> 1)) : 0u;
                stsm4(SM_A + rn * 128 + ((((lane & 1) * 4 + (lane >> 3)) ^ (rn & 7)) << 4), mi[0], mi[1], mi[2], mi[3]);
                const __nv_bfloat16 pn =
                    __float2bfloat16(fmaf(psum, __uint_as_float(lds32(SM_CONST + 2060)), __uint_as_float(pd)));
                if ((int)node < nown && (lane & 7) < 3) outp[node * 3 + t] = pn;
                if (++q == 4) break;
                grp = ngrp;
                rem = load_group(grp);
            }
        }
    }
    return __reduce_or_sync(0xffffffffu, badq);
}

__global__ void __launch_bounds__(NT, 1)
egnn_kernel(const __nv_bfloat16* __restrict__ h, const __nv_bfloat16* __restrict__ pos,
            const __nv_bfloat16* __restrict__ e_attr, const int* __restrict__ src, const int* __restrict__ dst,
            const __nv_bfloat16* __restrict__ w_e, const __nv_bfloat16* __restrict__ w_x,
            __nv_bfloat16* __restrict__ out, cudaTextureObject_t tex,
            const __grid_constant__ CUtensorMap map_h, const __grid_constant__ CUtensorMap map_wh) {
    extern __shared__ unsigned char smem_raw[];
    const int tid = threadIdx.x, lane = tid & 31;
    const int cta = blockIdx.x;
    const int node0 = cta * OWN;
    const int nown = min(OWN, N_NODES - node0);
    TSTAMP(0);

    auto bar_init = [](uint32_t bar, uint32_t bytes) {
        asm volatile("mbarrier.init.shared.b64 [%0], 1;" :: "r"(bar) : "memory");
        asm volatile("mbarrier.arrive.expect_tx.shared.b64 _, [%0], %1;" :: "r"(bar), "r"(bytes) : "memory");
    };
    if (tid == NT - 32) {
        const uint32_t ne = min(CH, N_EDGES - cta * CH);
        const uint32_t pbytes = (((node0 + nown) * 6 + 15) & ~15) - (node0 * 6 & ~15);
        bar_init(SM_BAR + 8, ne * 4);
        bar_init(SM_BAR + 16, ne * 6);
        bar_init(SM_BAR + 24, 131 * 128 + 16 + pbytes);
        asm volatile("fence.mbarrier_init.release.cluster;" ::: "memory");
        bulk_load(SM_ED, dst + cta * CH, ne * 4, SM_BAR + 8);
        bulk_load(SM_RE, g_epoch + cta, 16, SM_BAR + 24);
        bulk_load(SM_RP, reinterpret_cast<const char*>(pos) + (node0 * 6 & ~15), pbytes, SM_BAR + 24);
        bulk_load(SM_RX, w_x, 128, SM_BAR + 24);
        bulk_load(SM_RW, w_e, 130 * 128, SM_BAR + 24);
        bulk_load(SM_ES, src + cta * CH, ne * 4, SM_BAR + 16);
        bulk_load(SM_EA, e_attr + cta * CH, ne * 2, SM_BAR + 16);
    } else if (tid == NT - 96) {
        if ((uint32_t)__cvta_generic_to_shared(smem_raw) > SB) __trap();
        bar_init(SM_BAR, NPP * 64 + 16384);
        bar_init(SM_BAR + 32, NPP * 64);
        asm volatile("fence.mbarrier_init.release.cluster;" ::: "memory");
        asm volatile("prefetch.tensormap [%0];" :: "l"(&map_h) : "memory");
        asm volatile("prefetch.tensormap [%0];" :: "l"(&map_wh) : "memory");
    }
    if (tid < (SM_RUN - SM_CNT1) / 16) {
        const uint32_t z = tid < (SM_CNT2 - SM_CNT1) / 16 ? 1u : tid < (SM_DUMMY - SM_CNT1) / 16 ? 0u : 0x80000000u;
        sts128(SM_CNT1 + tid * 16, z, z, z, z);
    }
#pragma unroll
    for (int k = 0; k < 2; k++)
        if (k == 0 || tid < (NP * CELLU + 3) / 4 - NT) sts128(SM_META + (tid + k * NT) * 16, 0u, 0u, 0u, 0u);
    const int warp = uniform_warp(), wg = warp >> 2;
    __syncthreads();
    TSTAMP(1);
    if (tid < 2 * NP) g_cell[((size_t)(tid >> 1) * NP + cta) * CELLU + (tid & 1)] = make_uint4(0u, 0u, 0u, 0u);
    else if (tid < 2 * NP + 2) reinterpret_cast<uint4*>(g_mail + cta * MAILW)[tid & 1] = make_uint4(0u, 0u, 0u, 0u);
    else if (cta == 0 && tid < 2 * NP + 10) {
        g_B[(size_t)KILL * 8 + tid - (2 * NP + 2)] = make_uint4(0xF800F800u, 0xF800F800u, 0xF800F800u, 0xF800F800u);
        __threadfence();
    }
    uint32_t epoch;
    uint32_t tag;
    {
        uint4 vs[2], vd[2];
        uint2 ve[2];
        const int ne = min(CH, N_EDGES - cta * CH);
        uint32_t cell[EPT], rank[EPT];
        mbar_wait(SM_BAR + 8);
        TSTAMP(19);
#pragma unroll
        for (int k = 0; k < 2; k++) vd[k] = lds128(SM_ED + tid * 16 + k * (NT * 16));
        if (warp != NW - 1) {
            asm volatile("bar.arrive 11, %0;" :: "n"(NT), "r"(vd[0].x), "r"(vd[1].x) : "memory");
        } else {
            asm volatile("bar.sync 11, %0;" :: "n"(NT), "r"(vd[0].x), "r"(vd[1].x) : "memory");
            if (lane == 0) {
#pragma unroll
                for (int mt = 0; mt < H1TILES; mt++) tma_load(SM_H + mt * 8192, &map_h, node0 + mt * 64, SM_BAR + 32);
            }
            __syncwarp();
        }
#pragma unroll
        for (int k = 0; k < 2; k++) {
            const uint32_t dv[4] = {vd[k].x, vd[k].y, vd[k].z, vd[k].w};
            const bool ok = tid * 4 + k * (NT * 4) < ne;
#pragma unroll
            for (int q = 0; q < 4; q++) {
                cell[k * 4 + q] = dv[q] / OWN;
                rank[k * 4 + q] = atom_inc(ok ? SM_CNT1 + cell[k * 4 + q] * 4 : SM_DUMMY + lane * 4);
            }
        }
        int rmax = 0;
#pragma unroll
        for (int k = 0; k < 2; k++) {
            const uint32_t dv[4] = {vd[k].x, vd[k].y, vd[k].z, vd[k].w};
#pragma unroll
            for (int q = 0; q < 4; q++) {
                const uint32_t p = cell[k * 4 + q], rk = rank[k * 4 + q];
                const uint32_t u = (rk * 171u) >> 9, j = rk - 3u * u;
                const uint32_t ui = p * CELLU + u;
                rmax = max(rmax, (int)rk);
                red_or(rk < CELL ? SM_META + ui * 4 : SM_RUN + lane * 4, (dv[q] + 1u - p * OWN) << (9u * j));
                cell[k * 4 + q] = SM_STAGE + (ui * 4 + j) * 4;
            }
        }
    mbar_wait(SM_BAR + 24);
    if (tid >= NT - NPP) {
        const uint32_t n = tid - (NT - NPP), ok = (int)n < nown ? 0xffffffffu : 0u;
        const uint32_t pa = SM_RP + (node0 * 6 & 15) + n * 6;
        sts64(SM_POS + n * 8, (lds16(pa) | (lds16(pa + 2) << 16)) & ok, lds16(pa + 4) & ok);
    }
#pragma unroll
    for (int k = 0; k < 2; k++)
        if (k == 0 || tid < 1024 - NT) {
            const uint4 v = lds128(SM_RW + (tid + k * NT) * 16);
            sts128(SM_W + k * (NT * 16) + (tid >> 3) * 128 + (((tid & 7) ^ ((tid >> 3) & 7)) << 4), bmul2(v.x, 0x3F003F00u),
                   bmul2(v.y, 0x3F003F00u), bmul2(v.z, 0x3F003F00u), bmul2(v.w, 0x3F003F00u));
        }
    fence_async();
        if (warp == 8) const_phase();
        epoch = lds32(SM_RE);
        mbar_wait(SM_BAR + 16);
        TSTAMP(20);
#pragma unroll
        for (int k = 0; k < 2; k++) {
            vs[k] = lds128(SM_ES + tid * 16 + k * (NT * 16));
            ve[k] = lds64(SM_EA + tid * 8 + k * (NT * 8));
        }
        if (warp != NW - 1) {
                asm volatile("bar.arrive 9, %0;" :: "n"(NT), "r"(vs[0].x), "r"(vs[1].x), "r"(ve[0].x), "r"(ve[1].x) : "memory");
        } else {
            asm volatile("bar.sync 9, %0;" :: "n"(NT), "r"(vs[0].x), "r"(vs[1].x), "r"(ve[0].x), "r"(ve[1].x) : "memory");
            if (lane == 0) {
#pragma unroll
                for (int mt = H1TILES; mt < 6; mt++) tma_load(SM_H + mt * 8192, &map_h, node0 + mt * 64, mt < 3 ? SM_BAR + 32 : SM_BAR);
                tma_load(SM_W + 16384, &map_wh, 0, SM_BAR);
                tma_load(SM_W + 24576, &map_wh, 64, SM_BAR);
            }
            __syncwarp();
        }
        tag = (epoch % 0xffffu + 1u) << 16;
#pragma unroll
        for (int k = 0; k < 2; k++) {
            const uint32_t xv[4] = {__byte_perm(vs[k].x, ve[k].x, 0x5410), __byte_perm(vs[k].y, ve[k].x, 0x7610),
                                    __byte_perm(vs[k].z, ve[k].y, 0x5410), __byte_perm(vs[k].w, ve[k].y, 0x7610)};
#pragma unroll
            for (int q = 0; q < 4; q++) sts32_lt(rank[k * 4 + q], CELL, cell[k * 4 + q], xv[q]);
        }
        if (rmax >= CELL) {
#pragma unroll
            for (int k = 0; k < 2; k++) {
                const uint32_t dv[4] = {vd[k].x, vd[k].y, vd[k].z, vd[k].w};
                const uint32_t xv[4] = {__byte_perm(vs[k].x, ve[k].x, 0x5410), __byte_perm(vs[k].y, ve[k].x, 0x7610),
                                        __byte_perm(vs[k].z, ve[k].y, 0x5410), __byte_perm(vs[k].w, ve[k].y, 0x7610)};
#pragma unroll
                for (int q = 0; q < 4; q++)
                    if ((int)rank[k * 4 + q] >= CELL)
                        g_ovf[(size_t)cta * CH + atom_inc(F_NOVF)] = make_uint2(xv[q], dv[q]);
            }
            __threadfence();
        }
    }
    __syncthreads();
    TSTAMP(2);
    if (tid == 32) g_epoch[cta].x = epoch + 1;
    if (wg < 3) {
        node_phase(tag);
    } else {
        collect_phase(tag);
    }
    TSTAMP(6);
    if (wg >= 3) {
        asm volatile("bar.sync 3, %0;" :: "n"(NPP) : "memory");
        TSTAMP_T(7, 384);
        const int tid = threadIdx.x - (NT - NPP);
        const uint32_t deg = lds32(SM_CNT2 + tid * 4);
        uint32_t skey = 0;
        if (deg <= MAXD) skey = (deg + 1) >> 1;
        const uint32_t srank = atom_inc(SM_HIST + skey * 4);
        asm volatile("bar.sync 3, %0;" :: "n"(NPP) : "memory");
        const int c = lds32(SM_HIST + (31 - lane) * 4);
        int inc = c;
#pragma unroll
        for (int o = 1; o < 32; o <<= 1) {
            int v = __shfl_up_sync(0xffffffffu, inc, o);
            if (lane >= o) inc += v;
        }
        const int base = __shfl_sync(0xffffffffu, inc - c, 31 - skey);
        sts32(SM_ORD + (base + srank) * 4, (uint32_t)tid | (skey << 16));
        const int gs = (base + srank) & ~3;
        int l = 0;
#pragma unroll
        for (int o = 16; o > 0; o >>= 1)
            if (__shfl_sync(0xffffffffu, inc, l + o - 1) <= gs) l += o;
#pragma unroll 1
        for (int i = deg; i < 2 * max(31 - l, 2); i++) sts32(SM_REC + (tid * CAPN + i) * 4, KILL);
    } else {
        {
            const uint2 pp = lds64(SM_POS + tid * 8);
            const float x = __uint_as_float(pp.x << 16), y = __uint_as_float(pp.x & 0xffff0000u), z = __uint_as_float(pp.y << 16);
            if (!((x * x + y * y + z * z) * __uint_as_float(lds32(F_WDM)) <= 8192.f)) sts32(F_SLOW, 1u);
        }
        for (int run = tid; run < NP; run += NT - NPP) {
            const uint32_t v = poll_mail(run, tag);
            sts32(SM_RUN + run * 4, v);
            if (v & 0x8000u) sts32(F_GBIG, 1u);
        }
        TSTAMP(15);
    }
    __syncthreads();
    TSTAMP(8);

    const int myq = (lane >> 2) & 3;
    uint32_t rn = lds16(SM_ORD + (myq == 0 ? warp : 23 + 24 * myq - warp) * 16 + (lane & 3) * 4);
    rn |= (lds32(SM_CNT2 + rn * 4) > MAXD ? 1u << 16 : 0u) | ((int)rn >= nown ? 1u << 17 : 0u);
    uint32_t slow = 0xffffu;
    if (lds32(F_GBIG) != 0 && lds32(F_SLOW) == 0)
        slow = edge_phase(tex, out + (size_t)N_NODES * 64 + (size_t)node0 * 3, nown);
    TSTAMP_X(21, "max");
    slow = (slow | __ballot_sync(0xffffffffu, rn & (1u << 16))) & ~__ballot_sync(0xffffffffu, rn & (1u << 17)) & 0xffffu;
    rn &= 0xffffu;
    while (slow) {
        const int i = __ffs(slow) - 1;
        slow &= slow - 1;
        slow_node(__shfl_sync(0xffffffffu, rn, i), h, pos, w_e, w_x, out);
    }
    __syncwarp();

    {
        const uint32_t ro = rn * 128, sw = (lane >> 4) ^ (rn & 7);
        float acc[32];
        uint32_t a[4][4];
#pragma unroll
        for (int kk = 0; kk < 4; kk++) ldsm4(a[kk], SM_A + ro + ((sw ^ (2 * kk)) << 4));
        wg_fence();
        wg_n64r<0>(acc, a[0], mkdesc(SM_W + 24576));
#pragma unroll
        for (int kk = 1; kk < 4; kk++) wg_n64r<1>(acc, a[kk], mkdesc(SM_W + 24576 + kk * 2048));
        wg_commit();
        wg_wait0();
        uint32_t hf[4][4];
#pragma unroll
        for (int kk = 0; kk < 4; kk++) ldsm4(hf[kk], SM_H + ro + ((sw ^ (2 * kk)) << 4));
        wg_fence();
#pragma unroll
        for (int kk = 0; kk < 4; kk++) wg_n64r<1>(acc, hf[kk], mkdesc(SM_W + 16384 + kk * 2048));
        wg_commit();
        wg_wait0();
        fence_regs(acc);
#pragma unroll
        for (int kk = 0; kk < 4; kk++) {
#pragma unroll
            for (int i = 0; i < 4; i++) {
                asm volatile("" : "+r"(hf[kk][i]) :: "memory");
                hf[kk][i] = badd2(hf[kk][i], pack_bf(silu_half(0.5f * acc[8 * kk + 2 * i]), silu_half(0.5f * acc[8 * kk + 2 * i + 1])));
            }
            stsm4(SM_H + ro + ((sw ^ (2 * kk)) << 4), hf[kk][0], hf[kk][1], hf[kk][2], hf[kk][3]);
        }
        __syncwarp();
#pragma unroll
        for (int i = 0; i < 4; i++) {
            const uint32_t n = __shfl_sync(0xffffffffu, rn, 4 * i + (lane >> 3));
            const uint4 v = lds128(SM_H + n * 128 + (((lane & 7) ^ (n & 7)) << 4));
            if ((int)n < nown) reinterpret_cast<uint4*>(out + (size_t)(node0 + n) * 64)[lane & 7] = v;
        }
    }
    TSTAMP_X(23, "max");
}

typedef CUresult (*EncodeFn)(CUtensorMap*, CUtensorMapDataType, cuuint32_t, void*, const cuuint64_t*, const cuuint64_t*,
                             const cuuint32_t*, const cuuint32_t*, CUtensorMapInterleave, CUtensorMapSwizzle,
                             CUtensorMapL2promotion, CUtensorMapFloatOOBfill);

void encode_rows(EncodeFn fn, CUtensorMap* m, const void* base, int rows) {
    const cuuint64_t dim[2] = {64, (cuuint64_t)rows};
    const cuuint64_t stride[1] = {128};
    const cuuint32_t box[2] = {64, 64}, es[2] = {1, 1};
    fn(m, CU_TENSOR_MAP_DATA_TYPE_BFLOAT16, 2, const_cast<void*>(base), dim, stride, box, es,
       CU_TENSOR_MAP_INTERLEAVE_NONE, CU_TENSOR_MAP_SWIZZLE_128B, CU_TENSOR_MAP_L2_PROMOTION_NONE,
       CU_TENSOR_MAP_FLOAT_OOB_FILL_NONE);
}

}

extern "C" void kernel_launch(void* const* d_in, const int* in_sizes, int n_in, void* d_out, int out_size) {
    (void)in_sizes; (void)n_in; (void)out_size;
    static bool init_done = false;
    static cudaTextureObject_t tex = 0;
    static EncodeFn encode = nullptr;
    if (!init_done) {
        cudaFuncSetAttribute(egnn_kernel, cudaFuncAttributeMaxDynamicSharedMemorySize, SM_END);
        void* pB = nullptr;
        cudaGetSymbolAddress(&pB, g_B);
        cudaResourceDesc rd = {};
        rd.resType = cudaResourceTypeLinear;
        rd.res.linear.devPtr = pB;
        rd.res.linear.desc = cudaCreateChannelDesc(32, 32, 32, 32, cudaChannelFormatKindUnsigned);
        rd.res.linear.sizeInBytes = (size_t)BROWS * 128;
        cudaTextureDesc td = {};
        td.readMode = cudaReadModeElementType;
        cudaCreateTextureObject(&tex, &rd, &td, nullptr);
        cudaDriverEntryPointQueryResult qr;
        void* fn = nullptr;
        cudaGetDriverEntryPoint("cuTensorMapEncodeTiled", &fn, cudaEnableDefault, &qr);
        encode = (EncodeFn)fn;
        init_done = true;
    }
    CUtensorMap map_h, map_wh;
    encode_rows(encode, &map_h, d_in[0], N_NODES);
    encode_rows(encode, &map_wh, d_in[7], 128);
    egnn_kernel<<<NP, NT, SM_END>>>(
        (const __nv_bfloat16*)d_in[0], (const __nv_bfloat16*)d_in[1], (const __nv_bfloat16*)d_in[2],
        (const int*)d_in[3], (const int*)d_in[4], (const __nv_bfloat16*)d_in[5], (const __nv_bfloat16*)d_in[6],
        (__nv_bfloat16*)d_out, tex, map_h, map_wh);
}
```
